```python
import torch

def _softmax(x, axis=-1):
    return torch.softmax(x, dim=axis)
def _gelu(x):
    return torch.nn.functional.gelu(x, approximate="tanh")
def _silu(x):
    return torch.nn.functional.silu(x)
def _sigmoid(x):
    return torch.sigmoid(x)
def _layernorm(x, axis=-1, eps=1e-5):
    m = x.mean(dim=axis, keepdim=True)
    v = x.var(dim=axis, keepdim=True, unbiased=False)
    return (x - m) / torch.sqrt(v + eps)
def _scatter_add(tgt, idx, src, axis=0):
    return tgt.clone().index_add_(axis, idx, src)
def _segment_sum(src, seg, n):
    out = torch.zeros((n,) + src.shape[1:], dtype=src.dtype)
    return out.index_add_(0, seg, src)
def _pad(x, pw):
    flat = tuple(v for pair in reversed(pw) for v in pair)
    return torch.nn.functional.pad(x, flat)

kernel_name = 'recurrent_scan__spectral_gfnet__glu_gated_glu__prompt'

def setup_inputs():

    _w = (lambda a: (lambda t: t.to(torch.bfloat16) if t.is_floating_point() else t)(torch.as_tensor(a)))
    def _A_setup():
        B, S, D = 1, 2048, 640
        Df = D // 2 + 1
        return {
            "x": _w((lambda *s: torch.randn(*s, dtype=torch.bfloat16) * 0.05)(B, S, D)),
            "w_r": _w((lambda *s: torch.randn(*s, dtype=torch.bfloat16) * 0.05)(S, Df) * 0.02),
            "w_i": _w((lambda *s: torch.randn(*s, dtype=torch.bfloat16) * 0.05)(S, Df) * 0.02),
        }
    _A_in = _A_setup()

    def _B_setup():
        B, S, D, F = 1, 2048, 640, 1728
        return {
            "x": _w((lambda *s: torch.randn(*s, dtype=torch.bfloat16) * 0.05)(B, S, D)),
            "w_gate": _w((lambda *s: torch.randn(*s, dtype=torch.bfloat16) * 1.6)(D, F)),
            "w_up": _w((lambda *s: torch.randn(*s, dtype=torch.bfloat16) * 0.1)(D, F)),
            "w_down": _w((lambda *s: torch.randn(*s, dtype=torch.bfloat16) * 0.1)(F, D)),
        }
    _B_in = _B_setup()

    return {
        "A_x": _A_in["x"],
        "A_w_r": _A_in["w_r"],
        "A_w_i": _A_in["w_i"],
        "B_x": _B_in["x"],
        "B_w_gate": _B_in["w_gate"],
        "B_w_up": _B_in["w_up"],
        "B_w_down": _B_in["w_down"],
    }

def reference(A_x, A_w_r, A_w_i, B_x, B_w_gate, B_w_up, B_w_down):
    def _A_ref(x, w_r, w_i):
        B, S, D = x.shape
        X = (lambda x, axes=(-2,-1): torch.fft.rfft2(x.float(), dim=axes))(x, axes=(-2, -1))
        W = w_r + 1j * w_i
        X = X * W
        y = (lambda x, s, axes=(-2,-1): torch.fft.irfft2(x, s=s, dim=axes).to(torch.bfloat16))(X, (S, D), axes=(-2, -1))
        return y

    def _B_ref(x, w_gate, w_up, w_down):
        g = torch.einsum("bsd,df->bsf", x, w_gate)
        u = torch.einsum("bsd,df->bsf", x, w_up)
        h = _sigmoid(g) * u
        return torch.einsum("bsf,fd->bsd", h, w_down)

    x = A_x
    xn = _layernorm(x, axis=-1)
    s = _A_ref(xn, A_w_r, A_w_i)
    g = _silu(_B_ref(xn, B_w_gate, B_w_up, B_w_down))
    return x + s * g
```

```cpp
#include <cuda_runtime.h>
#include <cuda_bf16.h>
#include <cuda_fp16.h>
#include <cuda.h>
#include <stdint.h>

#define MC 0
namespace {

constexpr int S_ = 2048, D_ = 640, F_ = 1728, DF_ = 321;

__device__ __align__(1024) uint8_t g_h[32 * 27 * 8192];
__device__ __align__(1024) uint8_t g_wd[4 * 54 * 10240];
__device__ __align__(1024) uint8_t g_wc[60 * 8192];
__device__ __align__(1024) uint32_t g_z[320 * 2048];
__device__ __align__(1024) uint32_t g_cw[2 * 161 * 2048];
__device__ __align__(1024) uint8_t g_y[32 * 5 * 16384];
__device__ uint2 g_cs[5 * 2 * F_];
__device__ uint2 g_stat[S_];
__device__ __align__(128) unsigned g_flag[104 * 32];
__device__ unsigned g_epoch;
#define TS(i) do { } while (0)

__device__ __align__(128) const uint32_t g_tab[17024] = {
0x3c003c00,0x3c003c00,0x3c003c00,0x3c003c00,0x3bfa3c00,0x3bc73be7,0x3b643b9c,0x3ad23b21,0x3be73c00,0x3b213b9c,0x39a83a79,0x374438b4,0x3bc73c00,0x3a153b21,0x361f38b4,0xad053102,
0x3b9c3c00,0x38b43a79,0x34f2,0xb8b4b4f2,0x3b643c00,0x361f39a8,0xb61f0000,0xbb64b9a8,0x3b213c00,0x310238b4,0xb9a8b4f2,0xbbe7bb9c,0x3ad23c00,0xad053744,0xbb64b8b4,0xba15bbe7,
0x3a793c00,0xb4f234f2,0xbc00ba79,0xb4f2ba79,0x3a153c00,0xb82e3102,0xbb64bb9c,0x3378b744,0x39a83c00,0xb9a80000,0xb9a8bc00,0x39a88000,0x39323c00,0xbad2b102,0xb61fbb9c,0x3bc73744,
0x38b43c00,0xbb9cb4f2,0x8000ba79,0x3b9c3a79,0x382e3c00,0xbbfab744,0x361fb8b4,0x39323be7,0x37443c00,0xbbe7b8b4,0x39a8b4f2,0x31023b9c,0x361f3c00,0xbb64b9a8,0x3b648000,0xb61f39a8,
0x34f23c00,0xba79ba79,0x3c0034f2,0xba7934f2,0x33783c00,0xb932bb21,0x3b6438b4,0xbbfab102,0x31023c00,0xb744bb9c,0x39a83a79,0xbb21b8b4,0x2d053c00,0xb378bbe7,0x361f3b9c,0xb82ebb21,
0x3c00,0x8000bc00,0x3c00,0x8000bc00,0xad053c00,0x3378bbe7,0xb61f3b9c,0x382ebb21,0xb1023c00,0x3744bb9c,0xb9a83a79,0x3b21b8b4,0xb3783c00,0x3932bb21,0xbb6438b4,0x3bfab102,
0xb4f23c00,0x3a79ba79,0xbc0034f2,0x3a7934f2,0xb61f3c00,0x3b64b9a8,0xbb640000,0x361f39a8,0xb7443c00,0x3be7b8b4,0xb9a8b4f2,0xb1023b9c,0xb82e3c00,0x3bfab744,0xb61fb8b4,0xb9323be7,
0xb8b43c00,0x3b9cb4f2,0x8000ba79,0xbb9c3a79,0xb9323c00,0x3ad2b102,0x361fbb9c,0xbbc73744,0xb9a83c00,0x39a88000,0x39a8bc00,0xb9a80000,0xba153c00,0x382e3102,0x3b64bb9c,0xb378b744,
0xba793c00,0x34f234f2,0x3c00ba79,0x34f2ba79,0xbad23c00,0x2d053744,0x3b64b8b4,0x3a15bbe7,0xbb213c00,0xb10238b4,0x39a8b4f2,0x3be7bb9c,0xbb643c00,0xb61f39a8,0x361f8000,0x3b64b9a8,
0xbb9c3c00,0xb8b43a79,0x34f2,0x38b4b4f2,0xbbc73c00,0xba153b21,0xb61f38b4,0x2d053102,0xbbe73c00,0xbb213b9c,0xb9a83a79,0xb74438b4,0xbbfa3c00,0xbbc73be7,0xbb643b9c,0xbad23b21,
0xbc003c00,0xbc003c00,0xbc003c00,0xbc003c00,0xbbfa3c00,0xbbc73be7,0xbb643b9c,0xbad23b21,0xbbe73c00,0xbb213b9c,0xb9a83a79,0xb74438b4,0xbbc73c00,0xba153b21,0xb61f38b4,0x2d053102,
0xbb9c3c00,0xb8b43a79,0x800034f2,0x38b4b4f2,0xbb643c00,0xb61f39a8,0x361f0000,0x3b64b9a8,0xbb213c00,0xb10238b4,0x39a8b4f2,0x3be7bb9c,0xbad23c00,0x2d053744,0x3b64b8b4,0x3a15bbe7,
0xba793c00,0x34f234f2,0x3c00ba79,0x34f2ba79,0xba153c00,0x382e3102,0x3b64bb9c,0xb378b744,0xb9a83c00,0x39a80000,0x39a8bc00,0xb9a88000,0xb9323c00,0x3ad2b102,0x361fbb9c,0xbbc73744,
0xb8b43c00,0x3b9cb4f2,0xba79,0xbb9c3a79,0xb82e3c00,0x3bfab744,0xb61fb8b4,0xb9323be7,0xb7443c00,0x3be7b8b4,0xb9a8b4f2,0xb1023b9c,0xb61f3c00,0x3b64b9a8,0xbb648000,0x361f39a8,
0xb4f23c00,0x3a79ba79,0xbc0034f2,0x3a7934f2,0xb3783c00,0x3932bb21,0xbb6438b4,0x3bfab102,0xb1023c00,0x3744bb9c,0xb9a83a79,0x3b21b8b4,0xad053c00,0x3378bbe7,0xb61f3b9c,0x382ebb21,
0x80003c00,0xbc00,0x80003c00,0xbc00,0x2d053c00,0xb378bbe7,0x361f3b9c,0xb82ebb21,0x31023c00,0xb744bb9c,0x39a83a79,0xbb21b8b4,0x33783c00,0xb932bb21,0x3b6438b4,0xbbfab102,
0x34f23c00,0xba79ba79,0x3c0034f2,0xba7934f2,0x361f3c00,0xbb64b9a8,0x3b640000,0xb61f39a8,0x37443c00,0xbbe7b8b4,0x39a8b4f2,0x31023b9c,0x382e3c00,0xbbfab744,0x361fb8b4,0x39323be7,
0x38b43c00,0xbb9cb4f2,0xba79,0x3b9c3a79,0x39323c00,0xbad2b102,0xb61fbb9c,0x3bc73744,0x39a83c00,0xb9a88000,0xb9a8bc00,0x39a80000,0x3a153c00,0xb82e3102,0xbb64bb9c,0x3378b744,
0x3a793c00,0xb4f234f2,0xbc00ba79,0xb4f2ba79,0x3ad23c00,0xad053744,0xbb64b8b4,0xba15bbe7,0x3b213c00,0x310238b4,0xb9a8b4f2,0xbbe7bb9c,0x3b643c00,0x361f39a8,0xb61f8000,0xbb64b9a8,
0x3b9c3c00,0x38b43a79,0x800034f2,0xb8b4b4f2,0x3bc73c00,0x3a153b21,0x361f38b4,0xad053102,0x3be73c00,0x3b213b9c,0x39a83a79,0x374438b4,0x3bfa3c00,0x3bc73be7,0x3b643b9c,0x3ad23b21,
0x3c003c00,0x3c003c00,0x3c003c00,0x3c003c00,0x3a153a79,0x393239a8,0x382e38b4,0x361f3744,0x310234f2,0xb1020000,0xb744b4f2,0xb9a8b8b4,0xb82eb4f2,0xbad2b9a8,0xbbfabb9c,0xbb64bbe7,
0xbb9cba79,0xbb9cbc00,0xb8b4ba79,0x8000b4f2,0xbb64bc00,0xb61fb9a8,0x361f8000,0x3b6439a8,0xb744ba79,0x37448000,0x3be73a79,0x39a83b9c,0x3378b4f2,0x3bc739a8,0x39323b9c,0xb61f3102,
0x3a7934f2,0x3a793c00,0xb4f234f2,0xbc00ba79,0x3bfa3a79,0x2d0539a8,0xbbc7b8b4,0xb61fbb21,0x39a83c00,0xb9a80000,0xb9a8bc00,0x39a88000,0x2d053a79,0xbbfab9a8,0x3378b8b4,0x3b643b21,
0xb8b434f2,0xb8b4bc00,0x3b9c34f2,0x3a79,0xbbc7b4f2,0x3378b9a8,0x3a153b9c,0xbb64b102,0xbb21ba79,0x3b218000,0xb1023a79,0xb9a8bb9c,0xb61fbc00,0x3b6439a8,0xbb640000,0x361fb9a8,
0x34f2ba79,0x34f23c00,0xba79ba79,0x3c0034f2,0x3ad2b4f2,0xb82e39a8,0x2d05bb9c,0x361f3be7,0x3be734f2,0xbbe70000,0x3b21b4f2,0xb9a838b4,0x39323a79,0xba15b9a8,0x3ad238b4,0xbb64b744,
0x3c00,0x8000bc00,0x3c00,0x8000bc00,0xb9323a79,0x3a15b9a8,0xbad238b4,0x3b64b744,0xbbe734f2,0x3be78000,0xbb21b4f2,0x39a838b4,0xbad2b4f2,0x382e39a8,0xad05bb9c,0xb61f3be7,
0xb4f2ba79,0xb4f23c00,0x3a79ba79,0xbc0034f2,0x361fbc00,0xbb6439a8,0x3b648000,0xb61fb9a8,0x3b21ba79,0xbb210000,0x31023a79,0x39a8bb9c,0x3bc7b4f2,0xb378b9a8,0xba153b9c,0x3b64b102,
0x38b434f2,0x38b4bc00,0xbb9c34f2,0x3a79,0xad053a79,0x3bfab9a8,0xb378b8b4,0xbb643b21,0xb9a83c00,0x39a88000,0x39a8bc00,0xb9a80000,0xbbfa3a79,0xad0539a8,0x3bc7b8b4,0x361fbb21,
0xba7934f2,0xba793c00,0x34f234f2,0x3c00ba79,0xb378b4f2,0xbbc739a8,0xb9323b9c,0x361f3102,0x3744ba79,0xb7440000,0xbbe73a79,0xb9a83b9c,0x3b64bc00,0x361fb9a8,0xb61f0000,0xbb6439a8,
0x3b9cba79,0x3b9cbc00,0x38b4ba79,0x8000b4f2,0x382eb4f2,0x3ad2b9a8,0x3bfabb9c,0x3b64bbe7,0xb10234f2,0x31028000,0x3744b4f2,0x39a8b8b4,0xba153a79,0xb93239a8,0xb82e38b4,0xb61f3744,
0xbc003c00,0xbc003c00,0xbc003c00,0xbc003c00,0xba153a79,0xb93239a8,0xb82e38b4,0xb61f3744,0xb10234f2,0x31020000,0x3744b4f2,0x39a8b8b4,0x382eb4f2,0x3ad2b9a8,0x3bfabb9c,0x3b64bbe7,
0x3b9cba79,0x3b9cbc00,0x38b4ba79,0xb4f2,0x3b64bc00,0x361fb9a8,0xb61f8000,0xbb6439a8,0x3744ba79,0xb7448000,0xbbe73a79,0xb9a83b9c,0xb378b4f2,0xbbc739a8,0xb9323b9c,0x361f3102,
0xba7934f2,0xba793c00,0x34f234f2,0x3c00ba79,0xbbfa3a79,0xad0539a8,0x3bc7b8b4,0x361fbb21,0xb9a83c00,0x39a80000,0x39a8bc00,0xb9a88000,0xad053a79,0x3bfab9a8,0xb378b8b4,0xbb643b21,
0x38b434f2,0x38b4bc00,0xbb9c34f2,0x80003a79,0x3bc7b4f2,0xb378b9a8,0xba153b9c,0x3b64b102,0x3b21ba79,0xbb218000,0x31023a79,0x39a8bb9c,0x361fbc00,0xbb6439a8,0x3b640000,0xb61fb9a8,
0xb4f2ba79,0xb4f23c00,0x3a79ba79,0xbc0034f2,0xbad2b4f2,0x382e39a8,0xad05bb9c,0xb61f3be7,0xbbe734f2,0x3be70000,0xbb21b4f2,0x39a838b4,0xb9323a79,0x3a15b9a8,0xbad238b4,0x3b64b744,
0x80003c00,0xbc00,0x80003c00,0xbc00,0x39323a79,0xba15b9a8,0x3ad238b4,0xbb64b744,0x3be734f2,0xbbe78000,0x3b21b4f2,0xb9a838b4,0x3ad2b4f2,0xb82e39a8,0x2d05bb9c,0x361f3be7,
0x34f2ba79,0x34f23c00,0xba79ba79,0x3c0034f2,0xb61fbc00,0x3b6439a8,0xbb648000,0x361fb9a8,0xbb21ba79,0x3b210000,0xb1023a79,0xb9a8bb9c,0xbbc7b4f2,0x3378b9a8,0x3a153b9c,0xbb64b102,
0xb8b434f2,0xb8b4bc00,0x3b9c34f2,0x80003a79,0x2d053a79,0xbbfab9a8,0x3378b8b4,0x3b643b21,0x39a83c00,0xb9a88000,0xb9a8bc00,0x39a80000,0x3bfa3a79,0x2d0539a8,0xbbc7b8b4,0xb61fbb21,
0x3a7934f2,0x3a793c00,0xb4f234f2,0xbc00ba79,0x3378b4f2,0x3bc739a8,0x39323b9c,0xb61f3102,0xb744ba79,0x37440000,0x3be73a79,0x39a83b9c,0xbb64bc00,0xb61fb9a8,0x361f0000,0x3b6439a8,
0xbb9cba79,0xbb9cbc00,0xb8b4ba79,0xb4f2,0xb82eb4f2,0xbad2b9a8,0xbbfabb9c,0xbb64bbe7,0x310234f2,0xb1028000,0xb744b4f2,0xb9a8b8b4,0x3a153a79,0x393239a8,0x382e38b4,0x361f3744,
0x3c003c00,0x3c003c00,0x3c003c00,0x3c003c00,0x337834f2,0x2d053102,0xad050000,0xb378b102,0xbb21ba79,0xbbe7bb9c,0xbbe7bc00,0xbb21bb9c,0xb932ba79,0xb378b744,0x33788000,0x39323744,
0x38b434f2,0x3b9c3a79,0x3b9c3c00,0x38b43a79,0x3b643c00,0x361f39a8,0xb61f0000,0xbb64b9a8,0xb10234f2,0xbb21b8b4,0xbb21bc00,0xb102b8b4,0xbbfaba79,0xb82ebb21,0x382e8000,0x3bfa3b21,
0xb4f2ba79,0x3a7934f2,0x3a793c00,0xb4f234f2,0x3ad234f2,0x39323be7,0xb9320000,0xbad2bbe7,0x39a83c00,0xb9a80000,0xb9a8bc00,0x39a88000,0xb82e34f2,0xba15bbe7,0x3a158000,0x382e3be7,
0xbb9cba79,0x38b4b4f2,0x38b43c00,0xbb9cb4f2,0x2d05ba79,0x3ad23b21,0xbad20000,0xad05bb21,0x3be734f2,0xb74438b4,0xb744bc00,0x3be738b4,0x361f3c00,0xbb64b9a8,0x3b648000,0xb61f39a8,
0xba7934f2,0x34f2ba79,0x34f23c00,0xba79ba79,0xba15ba79,0x3bc73744,0xbbc70000,0x3a15b744,0x3744ba79,0xb1023b9c,0xb102bc00,0x37443b9c,0x3bc734f2,0xbbfab102,0x3bfa8000,0xbbc73102,
0x3c00,0x8000bc00,0x3c00,0x8000bc00,0xbbc734f2,0x3bfab102,0xbbfa0000,0x3bc73102,0xb744ba79,0x31023b9c,0x3102bc00,0xb7443b9c,0x3a15ba79,0xbbc73744,0x3bc78000,0xba15b744,
0x3a7934f2,0xb4f2ba79,0xb4f23c00,0x3a79ba79,0xb61f3c00,0x3b64b9a8,0xbb640000,0x361f39a8,0xbbe734f2,0x374438b4,0x3744bc00,0xbbe738b4,0xad05ba79,0xbad23b21,0x3ad28000,0x2d05bb21,
0x3b9cba79,0xb8b4b4f2,0xb8b43c00,0x3b9cb4f2,0x382e34f2,0x3a15bbe7,0xba150000,0xb82e3be7,0xb9a83c00,0x39a88000,0x39a8bc00,0xb9a80000,0xbad234f2,0xb9323be7,0x39328000,0x3ad2bbe7,
0x34f2ba79,0xba7934f2,0xba793c00,0x34f234f2,0x3bfaba79,0x382ebb21,0xb82e0000,0xbbfa3b21,0x310234f2,0x3b21b8b4,0x3b21bc00,0x3102b8b4,0xbb643c00,0xb61f39a8,0x361f8000,0x3b64b9a8,
0xb8b434f2,0xbb9c3a79,0xbb9c3c00,0xb8b43a79,0x3932ba79,0x3378b744,0xb3780000,0xb9323744,0x3b21ba79,0x3be7bb9c,0x3be7bc00,0x3b21bb9c,0xb37834f2,0xad053102,0x2d058000,0x3378b102,
0xbc003c00,0xbc003c00,0xbc003c00,0xbc003c00,0xb37834f2,0xad053102,0x2d050000,0x3378b102,0x3b21ba79,0x3be7bb9c,0x3be7bc00,0x3b21bb9c,0x3932ba79,0x3378b744,0xb3788000,0xb9323744,
0xb8b434f2,0xbb9c3a79,0xbb9c3c00,0xb8b43a79,0xbb643c00,0xb61f39a8,0x361f0000,0x3b64b9a8,0x310234f2,0x3b21b8b4,0x3b21bc00,0x3102b8b4,0x3bfaba79,0x382ebb21,0xb82e8000,0xbbfa3b21,
0x34f2ba79,0xba7934f2,0xba793c00,0x34f234f2,0xbad234f2,0xb9323be7,0x39320000,0x3ad2bbe7,0xb9a83c00,0x39a80000,0x39a8bc00,0xb9a88000,0x382e34f2,0x3a15bbe7,0xba158000,0xb82e3be7,
0x3b9cba79,0xb8b4b4f2,0xb8b43c00,0x3b9cb4f2,0xad05ba79,0xbad23b21,0x3ad20000,0x2d05bb21,0xbbe734f2,0x374438b4,0x3744bc00,0xbbe738b4,0xb61f3c00,0x3b64b9a8,0xbb648000,0x361f39a8,
0x3a7934f2,0xb4f2ba79,0xb4f23c00,0x3a79ba79,0x3a15ba79,0xbbc73744,0x3bc70000,0xba15b744,0xb744ba79,0x31023b9c,0x3102bc00,0xb7443b9c,0xbbc734f2,0x3bfab102,0xbbfa8000,0x3bc73102,
0x80003c00,0xbc00,0x80003c00,0xbc00,0x3bc734f2,0xbbfab102,0x3bfa0000,0xbbc73102,0x3744ba79,0xb1023b9c,0xb102bc00,0x37443b9c,0xba15ba79,0x3bc73744,0xbbc78000,0x3a15b744,
0xba7934f2,0x34f2ba79,0x34f23c00,0xba79ba79,0x361f3c00,0xbb64b9a8,0x3b640000,0xb61f39a8,0x3be734f2,0xb74438b4,0xb744bc00,0x3be738b4,0x2d05ba79,0x3ad23b21,0xbad28000,0xad05bb21,
0xbb9cba79,0x38b4b4f2,0x38b43c00,0xbb9cb4f2,0xb82e34f2,0xba15bbe7,0x3a150000,0x382e3be7,0x39a83c00,0xb9a88000,0xb9a8bc00,0x39a80000,0x3ad234f2,0x39323be7,0xb9328000,0xbad2bbe7,
0xb4f2ba79,0x3a7934f2,0x3a793c00,0xb4f234f2,0xbbfaba79,0xb82ebb21,0x382e0000,0x3bfa3b21,0xb10234f2,0xbb21b8b4,0xbb21bc00,0xb102b8b4,0x3b643c00,0x361f39a8,0xb61f8000,0xbb64b9a8,
0x38b434f2,0x3b9c3a79,0x3b9c3c00,0x38b43a79,0xb932ba79,0xb378b744,0x33780000,0x39323744,0xbb21ba79,0xbbe7bb9c,0xbbe7bc00,0xbb21bb9c,0x337834f2,0x2d053102,0xad058000,0xb378b102,
0x3c003c00,0x3c003c00,0x3c003c00,0x3c003c00,0xb61fb4f2,0xb82eb744,0xb932b8b4,0xba15b9a8,0xb9a8ba79,0xb744b8b4,0xb102b4f2,0x31028000,0x3b643a79,0x3bfa3be7,0x3ad23b9c,0x382e39a8,
0x34f2,0xb8b4b4f2,0xbb9cba79,0xbb9cbc00,0xbb64bc00,0xb61fb9a8,0x361f8000,0x3b6439a8,0x39a834f2,0x3be73b9c,0x37443a79,0xb7440000,0x361f3a79,0xb932b102,0xbbc7bb9c,0xb378b9a8,
0xbc00ba79,0xb4f2ba79,0x3a7934f2,0x3a793c00,0x361fb4f2,0x3bc73b21,0xad0538b4,0xbbfab9a8,0x39a83c00,0xb9a80000,0xb9a8bc00,0x39a88000,0xbb64b4f2,0xb378bb21,0x3bfa38b4,0xad0539a8,
0x8000ba79,0x3b9c3a79,0xb8b434f2,0xb8b4bc00,0x3b643a79,0xba153102,0xb378bb9c,0x3bc739a8,0xb9a834f2,0xb102bb9c,0x3b213a79,0xbb210000,0xb61fbc00,0x3b6439a8,0xbb640000,0x361fb9a8,
0x3c0034f2,0xba7934f2,0x34f2ba79,0x34f23c00,0xb61f3a79,0xad05bbe7,0x382e3b9c,0xbad2b9a8,0xb9a8ba79,0x3b2138b4,0xbbe7b4f2,0x3be78000,0x3b64b4f2,0xbad23744,0x3a15b8b4,0xb93239a8,
0x3c00,0x8000bc00,0x3c00,0x8000bc00,0xbb64b4f2,0x3ad23744,0xba15b8b4,0x393239a8,0x39a8ba79,0xbb2138b4,0x3be7b4f2,0xbbe70000,0x361f3a79,0x2d05bbe7,0xb82e3b9c,0x3ad2b9a8,
0xbc0034f2,0x3a7934f2,0xb4f2ba79,0xb4f23c00,0x361fbc00,0xbb6439a8,0x3b648000,0xb61fb9a8,0x39a834f2,0x3102bb9c,0xbb213a79,0x3b218000,0xbb643a79,0x3a153102,0x3378bb9c,0xbbc739a8,
0x8000ba79,0xbb9c3a79,0x38b434f2,0x38b4bc00,0x3b64b4f2,0x3378bb21,0xbbfa38b4,0x2d0539a8,0xb9a83c00,0x39a88000,0x39a8bc00,0xb9a80000,0xb61fb4f2,0xbbc73b21,0x2d0538b4,0x3bfab9a8,
0x3c00ba79,0x34f2ba79,0xba7934f2,0xba793c00,0xb61f3a79,0x3932b102,0x3bc7bb9c,0x3378b9a8,0xb9a834f2,0xbbe73b9c,0xb7443a79,0x37448000,0x3b64bc00,0x361fb9a8,0xb61f0000,0xbb6439a8,
0x34f2,0x38b4b4f2,0x3b9cba79,0x3b9cbc00,0xbb643a79,0xbbfa3be7,0xbad23b9c,0xb82e39a8,0x39a8ba79,0x3744b8b4,0x3102b4f2,0xb1020000,0x361fb4f2,0x382eb744,0x3932b8b4,0x3a15b9a8,
0xbc003c00,0xbc003c00,0xbc003c00,0xbc003c00,0x361fb4f2,0x382eb744,0x3932b8b4,0x3a15b9a8,0x39a8ba79,0x3744b8b4,0x3102b4f2,0xb1028000,0xbb643a79,0xbbfa3be7,0xbad23b9c,0xb82e39a8,
0x800034f2,0x38b4b4f2,0x3b9cba79,0x3b9cbc00,0x3b64bc00,0x361fb9a8,0xb61f8000,0xbb6439a8,0xb9a834f2,0xbbe73b9c,0xb7443a79,0x37440000,0xb61f3a79,0x3932b102,0x3bc7bb9c,0x3378b9a8,
0x3c00ba79,0x34f2ba79,0xba7934f2,0xba793c00,0xb61fb4f2,0xbbc73b21,0x2d0538b4,0x3bfab9a8,0xb9a83c00,0x39a80000,0x39a8bc00,0xb9a88000,0x3b64b4f2,0x3378bb21,0xbbfa38b4,0x2d0539a8,
0xba79,0xbb9c3a79,0x38b434f2,0x38b4bc00,0xbb643a79,0x3a153102,0x3378bb9c,0xbbc739a8,0x39a834f2,0x3102bb9c,0xbb213a79,0x3b210000,0x361fbc00,0xbb6439a8,0x3b640000,0xb61fb9a8,
0xbc0034f2,0x3a7934f2,0xb4f2ba79,0xb4f23c00,0x361f3a79,0x2d05bbe7,0xb82e3b9c,0x3ad2b9a8,0x39a8ba79,0xbb2138b4,0x3be7b4f2,0xbbe78000,0xbb64b4f2,0x3ad23744,0xba15b8b4,0x393239a8,
0x80003c00,0xbc00,0x80003c00,0xbc00,0x3b64b4f2,0xbad23744,0x3a15b8b4,0xb93239a8,0xb9a8ba79,0x3b2138b4,0xbbe7b4f2,0x3be70000,0xb61f3a79,0xad05bbe7,0x382e3b9c,0xbad2b9a8,
0x3c0034f2,0xba7934f2,0x34f2ba79,0x34f23c00,0xb61fbc00,0x3b6439a8,0xbb648000,0x361fb9a8,0xb9a834f2,0xb102bb9c,0x3b213a79,0xbb218000,0x3b643a79,0xba153102,0xb378bb9c,0x3bc739a8,
0xba79,0x3b9c3a79,0xb8b434f2,0xb8b4bc00,0xbb64b4f2,0xb378bb21,0x3bfa38b4,0xad0539a8,0x39a83c00,0xb9a88000,0xb9a8bc00,0x39a80000,0x361fb4f2,0x3bc73b21,0xad0538b4,0xbbfab9a8,
0xbc00ba79,0xb4f2ba79,0x3a7934f2,0x3a793c00,0x361f3a79,0xb932b102,0xbbc7bb9c,0xb378b9a8,0x39a834f2,0x3be73b9c,0x37443a79,0xb7448000,0xbb64bc00,0xb61fb9a8,0x361f0000,0x3b6439a8,
0x800034f2,0xb8b4b4f2,0xbb9cba79,0xbb9cbc00,0x3b643a79,0x3bfa3be7,0x3ad23b9c,0x382e39a8,0xb9a8ba79,0xb744b8b4,0xb102b4f2,0x31020000,0xb61fb4f2,0xb82eb744,0xb932b8b4,0xba15b9a8,
0x3c003c00,0x3c003c00,0x3c003c00,0x3c003c00,0xbad2ba79,0xbb64bb21,0xbbc7bb9c,0xbbfabbe7,0x374434f2,0x39a838b4,0x3b213a79,0x3be73b9c,0x2d0534f2,0xb61fb102,0xba15b8b4,0xbbc7bb21,
0xb8b4ba79,0x8000b4f2,0x38b434f2,0x3b9c3a79,0x3b643c00,0x361f39a8,0xb61f0000,0xbb64b9a8,0xbbe7ba79,0xb9a8bb9c,0x3102b4f2,0x3b2138b4,0x3a1534f2,0x3b643be7,0x2d0538b4,0xbad2b744,
0xb4f234f2,0xbc00ba79,0xb4f2ba79,0x3a7934f2,0xb378ba79,0x3b643744,0x382e3b9c,0xba15b102,0x39a83c00,0xb9a80000,0xb9a8bc00,0x39a88000,0xbbc7ba79,0x361fb744,0x3ad23b9c,0xb9323102,
0x3b9c34f2,0x3a79,0xbb9cba79,0x38b4b4f2,0xb93234f2,0xb61fbbe7,0x3bfa38b4,0xb82e3744,0x3102ba79,0x39a83b9c,0xbbe7b4f2,0x3744b8b4,0x361f3c00,0xbb64b9a8,0x3b648000,0xb61f39a8,
0xba79ba79,0x3c0034f2,0xba7934f2,0x34f2ba79,0x3bfa34f2,0xbb643102,0x3932b8b4,0xb3783b21,0xbb2134f2,0x39a8b8b4,0xb7443a79,0x3102bb9c,0x382eba79,0xb61f3b21,0x3378bb9c,0xad053be7,
0x3c00,0x8000bc00,0x3c00,0x8000bc00,0xb82eba79,0x361f3b21,0xb378bb9c,0x2d053be7,0x3b2134f2,0xb9a8b8b4,0x37443a79,0xb102bb9c,0xbbfa34f2,0x3b643102,0xb932b8b4,0x33783b21,
0x3a79ba79,0xbc0034f2,0x3a7934f2,0xb4f2ba79,0xb61f3c00,0x3b64b9a8,0xbb640000,0x361f39a8,0xb102ba79,0xb9a83b9c,0x3be7b4f2,0xb744b8b4,0x393234f2,0x361fbbe7,0xbbfa38b4,0x382e3744,
0xbb9c34f2,0x3a79,0x3b9cba79,0xb8b4b4f2,0x3bc7ba79,0xb61fb744,0xbad23b9c,0x39323102,0xb9a83c00,0x39a88000,0x39a8bc00,0xb9a80000,0x3378ba79,0xbb643744,0xb82e3b9c,0x3a15b102,
0x34f234f2,0x3c00ba79,0x34f2ba79,0xba7934f2,0xba1534f2,0xbb643be7,0xad0538b4,0x3ad2b744,0x3be7ba79,0x39a8bb9c,0xb102b4f2,0xbb2138b4,0xbb643c00,0xb61f39a8,0x361f8000,0x3b64b9a8,
0x38b4ba79,0x8000b4f2,0xb8b434f2,0xbb9c3a79,0xad0534f2,0x361fb102,0x3a15b8b4,0x3bc7bb21,0xb74434f2,0xb9a838b4,0xbb213a79,0xbbe73b9c,0x3ad2ba79,0x3b64bb21,0x3bc7bb9c,0x3bfabbe7,
0xbc003c00,0xbc003c00,0xbc003c00,0xbc003c00,0x3ad2ba79,0x3b64bb21,0x3bc7bb9c,0x3bfabbe7,0xb74434f2,0xb9a838b4,0xbb213a79,0xbbe73b9c,0xad0534f2,0x361fb102,0x3a15b8b4,0x3bc7bb21,
0x38b4ba79,0xb4f2,0xb8b434f2,0xbb9c3a79,0xbb643c00,0xb61f39a8,0x361f0000,0x3b64b9a8,0x3be7ba79,0x39a8bb9c,0xb102b4f2,0xbb2138b4,0xba1534f2,0xbb643be7,0xad0538b4,0x3ad2b744,
0x34f234f2,0x3c00ba79,0x34f2ba79,0xba7934f2,0x3378ba79,0xbb643744,0xb82e3b9c,0x3a15b102,0xb9a83c00,0x39a80000,0x39a8bc00,0xb9a88000,0x3bc7ba79,0xb61fb744,0xbad23b9c,0x39323102,
0xbb9c34f2,0x80003a79,0x3b9cba79,0xb8b4b4f2,0x393234f2,0x361fbbe7,0xbbfa38b4,0x382e3744,0xb102ba79,0xb9a83b9c,0x3be7b4f2,0xb744b8b4,0xb61f3c00,0x3b64b9a8,0xbb648000,0x361f39a8,
0x3a79ba79,0xbc0034f2,0x3a7934f2,0xb4f2ba79,0xbbfa34f2,0x3b643102,0xb932b8b4,0x33783b21,0x3b2134f2,0xb9a8b8b4,0x37443a79,0xb102bb9c,0xb82eba79,0x361f3b21,0xb378bb9c,0x2d053be7,
0x80003c00,0xbc00,0x80003c00,0xbc00,0x382eba79,0xb61f3b21,0x3378bb9c,0xad053be7,0xbb2134f2,0x39a8b8b4,0xb7443a79,0x3102bb9c,0x3bfa34f2,0xbb643102,0x3932b8b4,0xb3783b21,
0xba79ba79,0x3c0034f2,0xba7934f2,0x34f2ba79,0x361f3c00,0xbb64b9a8,0x3b640000,0xb61f39a8,0x3102ba79,0x39a83b9c,0xbbe7b4f2,0x3744b8b4,0xb93234f2,0xb61fbbe7,0x3bfa38b4,0xb82e3744,
0x3b9c34f2,0x80003a79,0xbb9cba79,0x38b4b4f2,0xbbc7ba79,0x361fb744,0x3ad23b9c,0xb9323102,0x39a83c00,0xb9a88000,0xb9a8bc00,0x39a80000,0xb378ba79,0x3b643744,0x382e3b9c,0xba15b102,
0xb4f234f2,0xbc00ba79,0xb4f2ba79,0x3a7934f2,0x3a1534f2,0x3b643be7,0x2d0538b4,0xbad2b744,0xbbe7ba79,0xb9a8bb9c,0x3102b4f2,0x3b2138b4,0x3b643c00,0x361f39a8,0xb61f8000,0xbb64b9a8,
0xb8b4ba79,0xb4f2,0x38b434f2,0x3b9c3a79,0x2d0534f2,0xb61fb102,0xba15b8b4,0xbbc7bb21,0x374434f2,0x39a838b4,0x3b213a79,0x3be73b9c,0xbad2ba79,0xbb64bb21,0xbbc7bb9c,0xbbfabbe7,
0x3c003c00,0x3c003c00,0x3c003c00,0x3c003c00,0xbbfabc00,0xbbc7bbe7,0xbb64bb9c,0xbad2bb21,0x3be73c00,0x3b213b9c,0x39a83a79,0x374438b4,0xbbc7bc00,0xba15bb21,0xb61fb8b4,0x2d05b102,
0x3b9c3c00,0x38b43a79,0x34f2,0xb8b4b4f2,0xbb64bc00,0xb61fb9a8,0x361f8000,0x3b6439a8,0x3b213c00,0x310238b4,0xb9a8b4f2,0xbbe7bb9c,0xbad2bc00,0x2d05b744,0x3b6438b4,0x3a153be7,
0x3a793c00,0xb4f234f2,0xbc00ba79,0xb4f2ba79,0xba15bc00,0x382eb102,0x3b643b9c,0xb3783744,0x39a83c00,0xb9a80000,0xb9a8bc00,0x39a88000,0xb932bc00,0x3ad23102,0x361f3b9c,0xbbc7b744,
0x38b43c00,0xbb9cb4f2,0x8000ba79,0x3b9c3a79,0xb82ebc00,0x3bfa3744,0xb61f38b4,0xb932bbe7,0x37443c00,0xbbe7b8b4,0x39a8b4f2,0x31023b9c,0xb61fbc00,0x3b6439a8,0xbb640000,0x361fb9a8,
0x34f23c00,0xba79ba79,0x3c0034f2,0xba7934f2,0xb378bc00,0x39323b21,0xbb64b8b4,0x3bfa3102,0x31023c00,0xb744bb9c,0x39a83a79,0xbb21b8b4,0xad05bc00,0x33783be7,0xb61fbb9c,0x382e3b21,
0x3c00,0x8000bc00,0x3c00,0x8000bc00,0x2d05bc00,0xb3783be7,0x361fbb9c,0xb82e3b21,0xb1023c00,0x3744bb9c,0xb9a83a79,0x3b21b8b4,0x3378bc00,0xb9323b21,0x3b64b8b4,0xbbfa3102,
0xb4f23c00,0x3a79ba79,0xbc0034f2,0x3a7934f2,0x361fbc00,0xbb6439a8,0x3b648000,0xb61fb9a8,0xb7443c00,0x3be7b8b4,0xb9a8b4f2,0xb1023b9c,0x382ebc00,0xbbfa3744,0x361f38b4,0x3932bbe7,
0xb8b43c00,0x3b9cb4f2,0x8000ba79,0xbb9c3a79,0x3932bc00,0xbad23102,0xb61f3b9c,0x3bc7b744,0xb9a83c00,0x39a88000,0x39a8bc00,0xb9a80000,0x3a15bc00,0xb82eb102,0xbb643b9c,0x33783744,
0xba793c00,0x34f234f2,0x3c00ba79,0x34f2ba79,0x3ad2bc00,0xad05b744,0xbb6438b4,0xba153be7,0xbb213c00,0xb10238b4,0x39a8b4f2,0x3be7bb9c,0x3b64bc00,0x361fb9a8,0xb61f0000,0xbb6439a8,
0xbb9c3c00,0xb8b43a79,0x34f2,0x38b4b4f2,0x3bc7bc00,0x3a15bb21,0x361fb8b4,0xad05b102,0xbbe73c00,0xbb213b9c,0xb9a83a79,0xb74438b4,0x3bfabc00,0x3bc7bbe7,0x3b64bb9c,0x3ad2bb21,
0xbc003c00,0xbc003c00,0xbc003c00,0xbc003c00,0x3bfabc00,0x3bc7bbe7,0x3b64bb9c,0x3ad2bb21,0xbbe73c00,0xbb213b9c,0xb9a83a79,0xb74438b4,0x3bc7bc00,0x3a15bb21,0x361fb8b4,0xad05b102,
0xbb9c3c00,0xb8b43a79,0x800034f2,0x38b4b4f2,0x3b64bc00,0x361fb9a8,0xb61f8000,0xbb6439a8,0xbb213c00,0xb10238b4,0x39a8b4f2,0x3be7bb9c,0x3ad2bc00,0xad05b744,0xbb6438b4,0xba153be7,
0xba793c00,0x34f234f2,0x3c00ba79,0x34f2ba79,0x3a15bc00,0xb82eb102,0xbb643b9c,0x33783744,0xb9a83c00,0x39a80000,0x39a8bc00,0xb9a88000,0x3932bc00,0xbad23102,0xb61f3b9c,0x3bc7b744,
0xb8b43c00,0x3b9cb4f2,0xba79,0xbb9c3a79,0x382ebc00,0xbbfa3744,0x361f38b4,0x3932bbe7,0xb7443c00,0x3be7b8b4,0xb9a8b4f2,0xb1023b9c,0x361fbc00,0xbb6439a8,0x3b640000,0xb61fb9a8,
0xb4f23c00,0x3a79ba79,0xbc0034f2,0x3a7934f2,0x3378bc00,0xb9323b21,0x3b64b8b4,0xbbfa3102,0xb1023c00,0x3744bb9c,0xb9a83a79,0x3b21b8b4,0x2d05bc00,0xb3783be7,0x361fbb9c,0xb82e3b21,
0x80003c00,0xbc00,0x80003c00,0xbc00,0xad05bc00,0x33783be7,0xb61fbb9c,0x382e3b21,0x31023c00,0xb744bb9c,0x39a83a79,0xbb21b8b4,0xb378bc00,0x39323b21,0xbb64b8b4,0x3bfa3102,
0x34f23c00,0xba79ba79,0x3c0034f2,0xba7934f2,0xb61fbc00,0x3b6439a8,0xbb648000,0x361fb9a8,0x37443c00,0xbbe7b8b4,0x39a8b4f2,0x31023b9c,0xb82ebc00,0x3bfa3744,0xb61f38b4,0xb932bbe7,
0x38b43c00,0xbb9cb4f2,0xba79,0x3b9c3a79,0xb932bc00,0x3ad23102,0x361f3b9c,0xbbc7b744,0x39a83c00,0xb9a88000,0xb9a8bc00,0x39a80000,0xba15bc00,0x382eb102,0x3b643b9c,0xb3783744,
0x3a793c00,0xb4f234f2,0xbc00ba79,0xb4f2ba79,0xbad2bc00,0x2d05b744,0x3b6438b4,0x3a153be7,0x3b213c00,0x310238b4,0xb9a8b4f2,0xbbe7bb9c,0xbb64bc00,0xb61fb9a8,0x361f0000,0x3b6439a8,
0x3b9c3c00,0x38b43a79,0x800034f2,0xb8b4b4f2,0xbbc7bc00,0xba15bb21,0xb61fb8b4,0x2d05b102,0x3be73c00,0x3b213b9c,0x39a83a79,0x374438b4,0xbbfabc00,0xbbc7bbe7,0xbb64bb9c,0xbad2bb21,
0x3c003c00,0x3c003c00,0x3c003c00,0x3c003c00,0xba15ba79,0xb932b9a8,0xb82eb8b4,0xb61fb744,0x310234f2,0xb1020000,0xb744b4f2,0xb9a8b8b4,0x382e34f2,0x3ad239a8,0x3bfa3b9c,0x3b643be7,
0xbb9cba79,0xbb9cbc00,0xb8b4ba79,0x8000b4f2,0x3b643c00,0x361f39a8,0xb61f0000,0xbb64b9a8,0xb744ba79,0x37448000,0x3be73a79,0x39a83b9c,0xb37834f2,0xbbc7b9a8,0xb932bb9c,0x361fb102,
0x3a7934f2,0x3a793c00,0xb4f234f2,0xbc00ba79,0xbbfaba79,0xad05b9a8,0x3bc738b4,0x361f3b21,0x39a83c00,0xb9a80000,0xb9a8bc00,0x39a88000,0xad05ba79,0x3bfa39a8,0xb37838b4,0xbb64bb21,
0xb8b434f2,0xb8b4bc00,0x3b9c34f2,0x3a79,0x3bc734f2,0xb37839a8,0xba15bb9c,0x3b643102,0xbb21ba79,0x3b218000,0xb1023a79,0xb9a8bb9c,0x361f3c00,0xbb64b9a8,0x3b648000,0xb61f39a8,
0x34f2ba79,0x34f23c00,0xba79ba79,0x3c0034f2,0xbad234f2,0x382eb9a8,0xad053b9c,0xb61fbbe7,0x3be734f2,0xbbe70000,0x3b21b4f2,0xb9a838b4,0xb932ba79,0x3a1539a8,0xbad2b8b4,0x3b643744,
0x3c00,0x8000bc00,0x3c00,0x8000bc00,0x3932ba79,0xba1539a8,0x3ad2b8b4,0xbb643744,0xbbe734f2,0x3be78000,0xbb21b4f2,0x39a838b4,0x3ad234f2,0xb82eb9a8,0x2d053b9c,0x361fbbe7,
0xb4f2ba79,0xb4f23c00,0x3a79ba79,0xbc0034f2,0xb61f3c00,0x3b64b9a8,0xbb640000,0x361f39a8,0x3b21ba79,0xbb210000,0x31023a79,0x39a8bb9c,0xbbc734f2,0x337839a8,0x3a15bb9c,0xbb643102,
0x38b434f2,0x38b4bc00,0xbb9c34f2,0x3a79,0x2d05ba79,0xbbfa39a8,0x337838b4,0x3b64bb21,0xb9a83c00,0x39a88000,0x39a8bc00,0xb9a80000,0x3bfaba79,0x2d05b9a8,0xbbc738b4,0xb61f3b21,
0xba7934f2,0xba793c00,0x34f234f2,0x3c00ba79,0x337834f2,0x3bc7b9a8,0x3932bb9c,0xb61fb102,0x3744ba79,0xb7440000,0xbbe73a79,0xb9a83b9c,0xbb643c00,0xb61f39a8,0x361f8000,0x3b64b9a8,
0x3b9cba79,0x3b9cbc00,0x38b4ba79,0x8000b4f2,0xb82e34f2,0xbad239a8,0xbbfa3b9c,0xbb643be7,0xb10234f2,0x31028000,0x3744b4f2,0x39a8b8b4,0x3a15ba79,0x3932b9a8,0x382eb8b4,0x361fb744,
0xbc003c00,0xbc003c00,0xbc003c00,0xbc003c00,0x3a15ba79,0x3932b9a8,0x382eb8b4,0x361fb744,0xb10234f2,0x31020000,0x3744b4f2,0x39a8b8b4,0xb82e34f2,0xbad239a8,0xbbfa3b9c,0xbb643be7,
0x3b9cba79,0x3b9cbc00,0x38b4ba79,0xb4f2,0xbb643c00,0xb61f39a8,0x361f0000,0x3b64b9a8,0x3744ba79,0xb7448000,0xbbe73a79,0xb9a83b9c,0x337834f2,0x3bc7b9a8,0x3932bb9c,0xb61fb102,
0xba7934f2,0xba793c00,0x34f234f2,0x3c00ba79,0x3bfaba79,0x2d05b9a8,0xbbc738b4,0xb61f3b21,0xb9a83c00,0x39a80000,0x39a8bc00,0xb9a88000,0x2d05ba79,0xbbfa39a8,0x337838b4,0x3b64bb21,
0x38b434f2,0x38b4bc00,0xbb9c34f2,0x80003a79,0xbbc734f2,0x337839a8,0x3a15bb9c,0xbb643102,0x3b21ba79,0xbb218000,0x31023a79,0x39a8bb9c,0xb61f3c00,0x3b64b9a8,0xbb648000,0x361f39a8,
0xb4f2ba79,0xb4f23c00,0x3a79ba79,0xbc0034f2,0x3ad234f2,0xb82eb9a8,0x2d053b9c,0x361fbbe7,0xbbe734f2,0x3be70000,0xbb21b4f2,0x39a838b4,0x3932ba79,0xba1539a8,0x3ad2b8b4,0xbb643744,
0x80003c00,0xbc00,0x80003c00,0xbc00,0xb932ba79,0x3a1539a8,0xbad2b8b4,0x3b643744,0x3be734f2,0xbbe78000,0x3b21b4f2,0xb9a838b4,0xbad234f2,0x382eb9a8,0xad053b9c,0xb61fbbe7,
0x34f2ba79,0x34f23c00,0xba79ba79,0x3c0034f2,0x361f3c00,0xbb64b9a8,0x3b640000,0xb61f39a8,0xbb21ba79,0x3b210000,0xb1023a79,0xb9a8bb9c,0x3bc734f2,0xb37839a8,0xba15bb9c,0x3b643102,
0xb8b434f2,0xb8b4bc00,0x3b9c34f2,0x80003a79,0xad05ba79,0x3bfa39a8,0xb37838b4,0xbb64bb21,0x39a83c00,0xb9a88000,0xb9a8bc00,0x39a80000,0xbbfaba79,0xad05b9a8,0x3bc738b4,0x361f3b21,
0x3a7934f2,0x3a793c00,0xb4f234f2,0xbc00ba79,0xb37834f2,0xbbc7b9a8,0xb932bb9c,0x361fb102,0xb744ba79,0x37440000,0x3be73a79,0x39a83b9c,0x3b643c00,0x361f39a8,0xb61f8000,0xbb64b9a8,
0xbb9cba79,0xbb9cbc00,0xb8b4ba79,0xb4f2,0x382e34f2,0x3ad239a8,0x3bfa3b9c,0x3b643be7,0x310234f2,0xb1028000,0xb744b4f2,0xb9a8b8b4,0xba15ba79,0xb932b9a8,0xb82eb8b4,0xb61fb744,
0x3c003c00,0x3c003c00,0x3c003c00,0x3c003c00,0xb378b4f2,0xad05b102,0x2d058000,0x33783102,0xbb21ba79,0xbbe7bb9c,0xbbe7bc00,0xbb21bb9c,0x39323a79,0x33783744,0xb3780000,0xb932b744,
0x38b434f2,0x3b9c3a79,0x3b9c3c00,0x38b43a79,0xbb64bc00,0xb61fb9a8,0x361f8000,0x3b6439a8,0xb10234f2,0xbb21b8b4,0xbb21bc00,0xb102b8b4,0x3bfa3a79,0x382e3b21,0xb82e0000,0xbbfabb21,
0xb4f2ba79,0x3a7934f2,0x3a793c00,0xb4f234f2,0xbad2b4f2,0xb932bbe7,0x39328000,0x3ad23be7,0x39a83c00,0xb9a80000,0xb9a8bc00,0x39a88000,0x382eb4f2,0x3a153be7,0xba150000,0xb82ebbe7,
0xbb9cba79,0x38b4b4f2,0x38b43c00,0xbb9cb4f2,0xad053a79,0xbad2bb21,0x3ad28000,0x2d053b21,0x3be734f2,0xb74438b4,0xb744bc00,0x3be738b4,0xb61fbc00,0x3b6439a8,0xbb640000,0x361fb9a8,
0xba7934f2,0x34f2ba79,0x34f23c00,0xba79ba79,0x3a153a79,0xbbc7b744,0x3bc78000,0xba153744,0x3744ba79,0xb1023b9c,0xb102bc00,0x37443b9c,0xbbc7b4f2,0x3bfa3102,0xbbfa0000,0x3bc7b102,
0x3c00,0x8000bc00,0x3c00,0x8000bc00,0x3bc7b4f2,0xbbfa3102,0x3bfa8000,0xbbc7b102,0xb744ba79,0x31023b9c,0x3102bc00,0xb7443b9c,0xba153a79,0x3bc7b744,0xbbc70000,0x3a153744,
0x3a7934f2,0xb4f2ba79,0xb4f23c00,0x3a79ba79,0x361fbc00,0xbb6439a8,0x3b648000,0xb61fb9a8,0xbbe734f2,0x374438b4,0x3744bc00,0xbbe738b4,0x2d053a79,0x3ad2bb21,0xbad20000,0xad053b21,
0x3b9cba79,0xb8b4b4f2,0xb8b43c00,0x3b9cb4f2,0xb82eb4f2,0xba153be7,0x3a158000,0x382ebbe7,0xb9a83c00,0x39a88000,0x39a8bc00,0xb9a80000,0x3ad2b4f2,0x3932bbe7,0xb9320000,0xbad23be7,
0x34f2ba79,0xba7934f2,0xba793c00,0x34f234f2,0xbbfa3a79,0xb82e3b21,0x382e8000,0x3bfabb21,0x310234f2,0x3b21b8b4,0x3b21bc00,0x3102b8b4,0x3b64bc00,0x361fb9a8,0xb61f0000,0xbb6439a8,
0xb8b434f2,0xbb9c3a79,0xbb9c3c00,0xb8b43a79,0xb9323a79,0xb3783744,0x33788000,0x3932b744,0x3b21ba79,0x3be7bb9c,0x3be7bc00,0x3b21bb9c,0x3378b4f2,0x2d05b102,0xad050000,0xb3783102,
0xbc003c00,0xbc003c00,0xbc003c00,0xbc003c00,0x3378b4f2,0x2d05b102,0xad058000,0xb3783102,0x3b21ba79,0x3be7bb9c,0x3be7bc00,0x3b21bb9c,0xb9323a79,0xb3783744,0x33780000,0x3932b744,
0xb8b434f2,0xbb9c3a79,0xbb9c3c00,0xb8b43a79,0x3b64bc00,0x361fb9a8,0xb61f8000,0xbb6439a8,0x310234f2,0x3b21b8b4,0x3b21bc00,0x3102b8b4,0xbbfa3a79,0xb82e3b21,0x382e0000,0x3bfabb21,
0x34f2ba79,0xba7934f2,0xba793c00,0x34f234f2,0x3ad2b4f2,0x3932bbe7,0xb9328000,0xbad23be7,0xb9a83c00,0x39a80000,0x39a8bc00,0xb9a88000,0xb82eb4f2,0xba153be7,0x3a150000,0x382ebbe7,
0x3b9cba79,0xb8b4b4f2,0xb8b43c00,0x3b9cb4f2,0x2d053a79,0x3ad2bb21,0xbad28000,0xad053b21,0xbbe734f2,0x374438b4,0x3744bc00,0xbbe738b4,0x361fbc00,0xbb6439a8,0x3b640000,0xb61fb9a8,
0x3a7934f2,0xb4f2ba79,0xb4f23c00,0x3a79ba79,0xba153a79,0x3bc7b744,0xbbc78000,0x3a153744,0xb744ba79,0x31023b9c,0x3102bc00,0xb7443b9c,0x3bc7b4f2,0xbbfa3102,0x3bfa0000,0xbbc7b102,
0x80003c00,0xbc00,0x80003c00,0xbc00,0xbbc7b4f2,0x3bfa3102,0xbbfa8000,0x3bc7b102,0x3744ba79,0xb1023b9c,0xb102bc00,0x37443b9c,0x3a153a79,0xbbc7b744,0x3bc70000,0xba153744,
0xba7934f2,0x34f2ba79,0x34f23c00,0xba79ba79,0xb61fbc00,0x3b6439a8,0xbb648000,0x361fb9a8,0x3be734f2,0xb74438b4,0xb744bc00,0x3be738b4,0xad053a79,0xbad2bb21,0x3ad20000,0x2d053b21,
0xbb9cba79,0x38b4b4f2,0x38b43c00,0xbb9cb4f2,0x382eb4f2,0x3a153be7,0xba158000,0xb82ebbe7,0x39a83c00,0xb9a88000,0xb9a8bc00,0x39a80000,0xbad2b4f2,0xb932bbe7,0x39320000,0x3ad23be7,
0xb4f2ba79,0x3a7934f2,0x3a793c00,0xb4f234f2,0x3bfa3a79,0x382e3b21,0xb82e8000,0xbbfabb21,0xb10234f2,0xbb21b8b4,0xbb21bc00,0xb102b8b4,0xbb64bc00,0xb61fb9a8,0x361f0000,0x3b6439a8,
0x38b434f2,0x3b9c3a79,0x3b9c3c00,0x38b43a79,0x39323a79,0x33783744,0xb3788000,0xb932b744,0xbb21ba79,0xbbe7bb9c,0xbbe7bc00,0xbb21bb9c,0xb378b4f2,0xad05b102,0x2d050000,0x33783102,
0x3c003c00,0x3c003c00,0x3c003c00,0x3c003c00,0x361f34f2,0x382e3744,0x393238b4,0x3a1539a8,0xb9a8ba79,0xb744b8b4,0xb102b4f2,0x31028000,0xbb64ba79,0xbbfabbe7,0xbad2bb9c,0xb82eb9a8,
0x34f2,0xb8b4b4f2,0xbb9cba79,0xbb9cbc00,0x3b643c00,0x361f39a8,0xb61f0000,0xbb64b9a8,0x39a834f2,0x3be73b9c,0x37443a79,0xb7440000,0xb61fba79,0x39323102,0x3bc73b9c,0x337839a8,
0xbc00ba79,0xb4f2ba79,0x3a7934f2,0x3a793c00,0xb61f34f2,0xbbc7bb21,0x2d05b8b4,0x3bfa39a8,0x39a83c00,0xb9a80000,0xb9a8bc00,0x39a88000,0x3b6434f2,0x33783b21,0xbbfab8b4,0x2d05b9a8,
0x8000ba79,0x3b9c3a79,0xb8b434f2,0xb8b4bc00,0xbb64ba79,0x3a15b102,0x33783b9c,0xbbc7b9a8,0xb9a834f2,0xb102bb9c,0x3b213a79,0xbb210000,0x361f3c00,0xbb64b9a8,0x3b648000,0xb61f39a8,
0x3c0034f2,0xba7934f2,0x34f2ba79,0x34f23c00,0x361fba79,0x2d053be7,0xb82ebb9c,0x3ad239a8,0xb9a8ba79,0x3b2138b4,0xbbe7b4f2,0x3be78000,0xbb6434f2,0x3ad2b744,0xba1538b4,0x3932b9a8,
0x3c00,0x8000bc00,0x3c00,0x8000bc00,0x3b6434f2,0xbad2b744,0x3a1538b4,0xb932b9a8,0x39a8ba79,0xbb2138b4,0x3be7b4f2,0xbbe70000,0xb61fba79,0xad053be7,0x382ebb9c,0xbad239a8,
0xbc0034f2,0x3a7934f2,0xb4f2ba79,0xb4f23c00,0xb61f3c00,0x3b64b9a8,0xbb640000,0x361f39a8,0x39a834f2,0x3102bb9c,0xbb213a79,0x3b218000,0x3b64ba79,0xba15b102,0xb3783b9c,0x3bc7b9a8,
0x8000ba79,0xbb9c3a79,0x38b434f2,0x38b4bc00,0xbb6434f2,0xb3783b21,0x3bfab8b4,0xad05b9a8,0xb9a83c00,0x39a88000,0x39a8bc00,0xb9a80000,0x361f34f2,0x3bc7bb21,0xad05b8b4,0xbbfa39a8,
0x3c00ba79,0x34f2ba79,0xba7934f2,0xba793c00,0x361fba79,0xb9323102,0xbbc73b9c,0xb37839a8,0xb9a834f2,0xbbe73b9c,0xb7443a79,0x37448000,0xbb643c00,0xb61f39a8,0x361f8000,0x3b64b9a8,
0x34f2,0x38b4b4f2,0x3b9cba79,0x3b9cbc00,0x3b64ba79,0x3bfabbe7,0x3ad2bb9c,0x382eb9a8,0x39a8ba79,0x3744b8b4,0x3102b4f2,0xb1020000,0xb61f34f2,0xb82e3744,0xb93238b4,0xba1539a8,
0xbc003c00,0xbc003c00,0xbc003c00,0xbc003c00,0xb61f34f2,0xb82e3744,0xb93238b4,0xba1539a8,0x39a8ba79,0x3744b8b4,0x3102b4f2,0xb1028000,0x3b64ba79,0x3bfabbe7,0x3ad2bb9c,0x382eb9a8,
0x800034f2,0x38b4b4f2,0x3b9cba79,0x3b9cbc00,0xbb643c00,0xb61f39a8,0x361f0000,0x3b64b9a8,0xb9a834f2,0xbbe73b9c,0xb7443a79,0x37440000,0x361fba79,0xb9323102,0xbbc73b9c,0xb37839a8,
0x3c00ba79,0x34f2ba79,0xba7934f2,0xba793c00,0x361f34f2,0x3bc7bb21,0xad05b8b4,0xbbfa39a8,0xb9a83c00,0x39a80000,0x39a8bc00,0xb9a88000,0xbb6434f2,0xb3783b21,0x3bfab8b4,0xad05b9a8,
0xba79,0xbb9c3a79,0x38b434f2,0x38b4bc00,0x3b64ba79,0xba15b102,0xb3783b9c,0x3bc7b9a8,0x39a834f2,0x3102bb9c,0xbb213a79,0x3b210000,0xb61f3c00,0x3b64b9a8,0xbb648000,0x361f39a8,
0xbc0034f2,0x3a7934f2,0xb4f2ba79,0xb4f23c00,0xb61fba79,0xad053be7,0x382ebb9c,0xbad239a8,0x39a8ba79,0xbb2138b4,0x3be7b4f2,0xbbe78000,0x3b6434f2,0xbad2b744,0x3a1538b4,0xb932b9a8,
0x80003c00,0xbc00,0x80003c00,0xbc00,0xbb6434f2,0x3ad2b744,0xba1538b4,0x3932b9a8,0xb9a8ba79,0x3b2138b4,0xbbe7b4f2,0x3be70000,0x361fba79,0x2d053be7,0xb82ebb9c,0x3ad239a8,
0x3c0034f2,0xba7934f2,0x34f2ba79,0x34f23c00,0x361f3c00,0xbb64b9a8,0x3b640000,0xb61f39a8,0xb9a834f2,0xb102bb9c,0x3b213a79,0xbb218000,0xbb64ba79,0x3a15b102,0x33783b9c,0xbbc7b9a8,
0xba79,0x3b9c3a79,0xb8b434f2,0xb8b4bc00,0x3b6434f2,0x33783b21,0xbbfab8b4,0x2d05b9a8,0x39a83c00,0xb9a88000,0xb9a8bc00,0x39a80000,0xb61f34f2,0xbbc7bb21,0x2d05b8b4,0x3bfa39a8,
0xbc00ba79,0xb4f2ba79,0x3a7934f2,0x3a793c00,0xb61fba79,0x39323102,0x3bc73b9c,0x337839a8,0x39a834f2,0x3be73b9c,0x37443a79,0xb7448000,0x3b643c00,0x361f39a8,0xb61f8000,0xbb64b9a8,
0x800034f2,0xb8b4b4f2,0xbb9cba79,0xbb9cbc00,0xbb64ba79,0xbbfabbe7,0xbad2bb9c,0xb82eb9a8,0xb9a8ba79,0xb744b8b4,0xb102b4f2,0x31020000,0x361f34f2,0x382e3744,0x393238b4,0x3a1539a8,
0x3c003c00,0x3c003c00,0x3c003c00,0x3c003c00,0x3ad23a79,0x3b643b21,0x3bc73b9c,0x3bfa3be7,0x374434f2,0x39a838b4,0x3b213a79,0x3be73b9c,0xad05b4f2,0x361f3102,0x3a1538b4,0x3bc73b21,
0xb8b4ba79,0x8000b4f2,0x38b434f2,0x3b9c3a79,0xbb64bc00,0xb61fb9a8,0x361f8000,0x3b6439a8,0xbbe7ba79,0xb9a8bb9c,0x3102b4f2,0x3b2138b4,0xba15b4f2,0xbb64bbe7,0xad05b8b4,0x3ad23744,
0xb4f234f2,0xbc00ba79,0xb4f2ba79,0x3a7934f2,0x33783a79,0xbb64b744,0xb82ebb9c,0x3a153102,0x39a83c00,0xb9a80000,0xb9a8bc00,0x39a88000,0x3bc73a79,0xb61f3744,0xbad2bb9c,0x3932b102,
0x3b9c34f2,0x3a79,0xbb9cba79,0x38b4b4f2,0x3932b4f2,0x361f3be7,0xbbfab8b4,0x382eb744,0x3102ba79,0x39a83b9c,0xbbe7b4f2,0x3744b8b4,0xb61fbc00,0x3b6439a8,0xbb640000,0x361fb9a8,
0xba79ba79,0x3c0034f2,0xba7934f2,0x34f2ba79,0xbbfab4f2,0x3b64b102,0xb93238b4,0x3378bb21,0xbb2134f2,0x39a8b8b4,0xb7443a79,0x3102bb9c,0xb82e3a79,0x361fbb21,0xb3783b9c,0x2d05bbe7,
0x3c00,0x8000bc00,0x3c00,0x8000bc00,0x382e3a79,0xb61fbb21,0x33783b9c,0xad05bbe7,0x3b2134f2,0xb9a8b8b4,0x37443a79,0xb102bb9c,0x3bfab4f2,0xbb64b102,0x393238b4,0xb378bb21,
0x3a79ba79,0xbc0034f2,0x3a7934f2,0xb4f2ba79,0x361fbc00,0xbb6439a8,0x3b648000,0xb61fb9a8,0xb102ba79,0xb9a83b9c,0x3be7b4f2,0xb744b8b4,0xb932b4f2,0xb61f3be7,0x3bfab8b4,0xb82eb744,
0xbb9c34f2,0x3a79,0x3b9cba79,0xb8b4b4f2,0xbbc73a79,0x361f3744,0x3ad2bb9c,0xb932b102,0xb9a83c00,0x39a88000,0x39a8bc00,0xb9a80000,0xb3783a79,0x3b64b744,0x382ebb9c,0xba153102,
0x34f234f2,0x3c00ba79,0x34f2ba79,0xba7934f2,0x3a15b4f2,0x3b64bbe7,0x2d05b8b4,0xbad23744,0x3be7ba79,0x39a8bb9c,0xb102b4f2,0xbb2138b4,0x3b64bc00,0x361fb9a8,0xb61f0000,0xbb6439a8,
0x38b4ba79,0x8000b4f2,0xb8b434f2,0xbb9c3a79,0x2d05b4f2,0xb61f3102,0xba1538b4,0xbbc73b21,0xb74434f2,0xb9a838b4,0xbb213a79,0xbbe73b9c,0xbad23a79,0xbb643b21,0xbbc73b9c,0xbbfa3be7,
0xbc003c00,0xbc003c00,0xbc003c00,0xbc003c00,0xbad23a79,0xbb643b21,0xbbc73b9c,0xbbfa3be7,0xb74434f2,0xb9a838b4,0xbb213a79,0xbbe73b9c,0x2d05b4f2,0xb61f3102,0xba1538b4,0xbbc73b21,
0x38b4ba79,0xb4f2,0xb8b434f2,0xbb9c3a79,0x3b64bc00,0x361fb9a8,0xb61f8000,0xbb6439a8,0x3be7ba79,0x39a8bb9c,0xb102b4f2,0xbb2138b4,0x3a15b4f2,0x3b64bbe7,0x2d05b8b4,0xbad23744,
0x34f234f2,0x3c00ba79,0x34f2ba79,0xba7934f2,0xb3783a79,0x3b64b744,0x382ebb9c,0xba153102,0xb9a83c00,0x39a80000,0x39a8bc00,0xb9a88000,0xbbc73a79,0x361f3744,0x3ad2bb9c,0xb932b102,
0xbb9c34f2,0x80003a79,0x3b9cba79,0xb8b4b4f2,0xb932b4f2,0xb61f3be7,0x3bfab8b4,0xb82eb744,0xb102ba79,0xb9a83b9c,0x3be7b4f2,0xb744b8b4,0x361fbc00,0xbb6439a8,0x3b640000,0xb61fb9a8,
0x3a79ba79,0xbc0034f2,0x3a7934f2,0xb4f2ba79,0x3bfab4f2,0xbb64b102,0x393238b4,0xb378bb21,0x3b2134f2,0xb9a8b8b4,0x37443a79,0xb102bb9c,0x382e3a79,0xb61fbb21,0x33783b9c,0xad05bbe7,
0x80003c00,0xbc00,0x80003c00,0xbc00,0xb82e3a79,0x361fbb21,0xb3783b9c,0x2d05bbe7,0xbb2134f2,0x39a8b8b4,0xb7443a79,0x3102bb9c,0xbbfab4f2,0x3b64b102,0xb93238b4,0x3378bb21,
0xba79ba79,0x3c0034f2,0xba7934f2,0x34f2ba79,0xb61fbc00,0x3b6439a8,0xbb648000,0x361fb9a8,0x3102ba79,0x39a83b9c,0xbbe7b4f2,0x3744b8b4,0x3932b4f2,0x361f3be7,0xbbfab8b4,0x382eb744,
0x3b9c34f2,0x80003a79,0xbb9cba79,0x38b4b4f2,0x3bc73a79,0xb61f3744,0xbad2bb9c,0x3932b102,0x39a83c00,0xb9a88000,0xb9a8bc00,0x39a80000,0x33783a79,0xbb64b744,0xb82ebb9c,0x3a153102,
0xb4f234f2,0xbc00ba79,0xb4f2ba79,0x3a7934f2,0xba15b4f2,0xbb64bbe7,0xad05b8b4,0x3ad23744,0xbbe7ba79,0xb9a8bb9c,0x3102b4f2,0x3b2138b4,0xbb64bc00,0xb61fb9a8,0x361f0000,0x3b6439a8,
0xb8b4ba79,0xb4f2,0x38b434f2,0x3b9c3a79,0xad05b4f2,0x361f3102,0x3a1538b4,0x3bc73b21,0x374434f2,0x39a838b4,0x3b213a79,0x3be73b9c,0x3ad23a79,0x3b643b21,0x3bc73b9c,0x3bfa3be7,
0x0,0x0,0x0,0x0,0x2d050000,0x33783102,0x361f34f2,0x382e3744,0x31020000,0x374434f2,0x39a838b4,0x3b213a79,0x33780000,0x39323744,0x3b643a79,0x3bfa3be7,
0x34f20000,0x3a7938b4,0x3c003b9c,0x3a793b9c,0x361f0000,0x3b6439a8,0x3b643c00,0x361f39a8,0x37440000,0x3be73a79,0x39a83b9c,0xb10234f2,0x382e0000,0x3bfa3b21,0x361f3a79,0xb932b102,
0x38b40000,0x3b9c3b9c,0x38b4,0xbb9cb8b4,0x39320000,0x3ad23be7,0xb61f34f2,0xbbc7bb21,0x39a80000,0x39a83c00,0xb9a80000,0xb9a8bc00,0x3a150000,0x382e3be7,0xbb64b4f2,0xb378bb21,
0x3a790000,0x34f23b9c,0xbc00b8b4,0x34f2b8b4,0x3ad20000,0x2d053b21,0xbb64ba79,0x3a15b102,0x3b210000,0xb1023a79,0xb9a8bb9c,0x3be734f2,0x3b640000,0xb61f39a8,0xb61fbc00,0x3b6439a8,
0x3b9c0000,0xb8b438b4,0xbb9c,0x38b43b9c,0x3bc70000,0xba153744,0x361fba79,0x2d053be7,0x3be70000,0xbb2134f2,0x39a8b8b4,0xb7443a79,0x3bfa0000,0xbbc73102,0x3b64b4f2,0xbad23744,
0x3c000000,0xbc000000,0x3c000000,0xbc000000,0x3bfa0000,0xbbc7b102,0x3b6434f2,0xbad2b744,0x3be70000,0xbb21b4f2,0x39a838b4,0xb744ba79,0x3bc70000,0xba15b744,0x361f3a79,0x2d05bbe7,
0x3b9c0000,0xb8b4b8b4,0x3b9c,0x38b4bb9c,0x3b640000,0xb61fb9a8,0xb61f3c00,0x3b64b9a8,0x3b210000,0xb102ba79,0xb9a83b9c,0x3be7b4f2,0x3ad20000,0x2d05bb21,0xbb643a79,0x3a153102,
0x3a790000,0x34f2bb9c,0xbc0038b4,0x34f238b4,0x3a150000,0x382ebbe7,0xbb6434f2,0xb3783b21,0x39a80000,0x39a8bc00,0xb9a80000,0xb9a83c00,0x39320000,0x3ad2bbe7,0xb61fb4f2,0xbbc73b21,
0x38b40000,0x3b9cbb9c,0xb8b4,0xbb9c38b4,0x382e0000,0x3bfabb21,0x361fba79,0xb9323102,0x37440000,0x3be7ba79,0x39a8bb9c,0xb102b4f2,0x361f0000,0x3b64b9a8,0x3b64bc00,0x361fb9a8,
0x34f20000,0x3a79b8b4,0x3c00bb9c,0x3a79bb9c,0x33780000,0x3932b744,0x3b64ba79,0x3bfabbe7,0x31020000,0x3744b4f2,0x39a8b8b4,0x3b21ba79,0x2d050000,0x3378b102,0x361fb4f2,0x382eb744,
0x0,0x0,0x0,0x0,0xad050000,0xb3783102,0xb61f34f2,0xb82e3744,0xb1020000,0xb74434f2,0xb9a838b4,0xbb213a79,0xb3780000,0xb9323744,0xbb643a79,0xbbfa3be7,
0xb4f20000,0xba7938b4,0xbc003b9c,0xba793b9c,0xb61f0000,0xbb6439a8,0xbb643c00,0xb61f39a8,0xb7440000,0xbbe73a79,0xb9a83b9c,0x310234f2,0xb82e0000,0xbbfa3b21,0xb61f3a79,0x3932b102,
0xb8b40000,0xbb9c3b9c,0x38b4,0x3b9cb8b4,0xb9320000,0xbad23be7,0x361f34f2,0x3bc7bb21,0xb9a80000,0xb9a83c00,0x39a80000,0x39a8bc00,0xba150000,0xb82e3be7,0x3b64b4f2,0x3378bb21,
0xba790000,0xb4f23b9c,0x3c00b8b4,0xb4f2b8b4,0xbad20000,0xad053b21,0x3b64ba79,0xba15b102,0xbb210000,0x31023a79,0x39a8bb9c,0xbbe734f2,0xbb640000,0x361f39a8,0x361fbc00,0xbb6439a8,
0xbb9c0000,0x38b438b4,0xbb9c,0xb8b43b9c,0xbbc70000,0x3a153744,0xb61fba79,0xad053be7,0xbbe70000,0x3b2134f2,0xb9a8b8b4,0x37443a79,0xbbfa0000,0x3bc73102,0xbb64b4f2,0x3ad23744,
0xbc000000,0x3c000000,0xbc000000,0x3c000000,0xbbfa0000,0x3bc7b102,0xbb6434f2,0x3ad2b744,0xbbe70000,0x3b21b4f2,0xb9a838b4,0x3744ba79,0xbbc70000,0x3a15b744,0xb61f3a79,0xad05bbe7,
0xbb9c0000,0x38b4b8b4,0x3b9c,0xb8b4bb9c,0xbb640000,0x361fb9a8,0x361f3c00,0xbb64b9a8,0xbb210000,0x3102ba79,0x39a83b9c,0xbbe7b4f2,0xbad20000,0xad05bb21,0x3b643a79,0xba153102,
0xba790000,0xb4f2bb9c,0x3c0038b4,0xb4f238b4,0xba150000,0xb82ebbe7,0x3b6434f2,0x33783b21,0xb9a80000,0xb9a8bc00,0x39a80000,0x39a83c00,0xb9320000,0xbad2bbe7,0x361fb4f2,0x3bc73b21,
0xb8b40000,0xbb9cbb9c,0xb8b4,0x3b9c38b4,0xb82e0000,0xbbfabb21,0xb61fba79,0x39323102,0xb7440000,0xbbe7ba79,0xb9a8bb9c,0x3102b4f2,0xb61f0000,0xbb64b9a8,0xbb64bc00,0xb61fb9a8,
0xb4f20000,0xba79b8b4,0xbc00bb9c,0xba79bb9c,0xb3780000,0xb932b744,0xbb64ba79,0xbbfabbe7,0xb1020000,0xb744b4f2,0xb9a8b8b4,0xbb21ba79,0xad050000,0xb378b102,0xb61fb4f2,0xb82eb744,
0x0,0x0,0x0,0x0,0x393238b4,0x3a1539a8,0x3ad23a79,0x3b643b21,0x3be73b9c,0x3be73c00,0x3b213b9c,0x39a83a79,0x3ad23b9c,0x382e39a8,0x2d0534f2,0xb61fb102,
0x34f238b4,0xb4f20000,0xba79b8b4,0xbc00bb9c,0xb61f0000,0xbb64b9a8,0xbb64bc00,0xb61fb9a8,0xbb21b8b4,0xbb21bc00,0xb102b8b4,0x39a834f2,0xbbc7bb9c,0xb378b9a8,0x3a1534f2,0x3b643be7,
0xb8b4bb9c,0x38b40000,0x3b9c3b9c,0x38b4,0x2d05b8b4,0x3bfa39a8,0x33783a79,0xbb64b744,0x39a80000,0x39a83c00,0xb9a80000,0xb9a8bc00,0x3bfa38b4,0xad0539a8,0xbbc7ba79,0x361fb744,
0x3a793b9c,0xba790000,0xb4f2bb9c,0x3c0038b4,0x33783b9c,0xbbc7b9a8,0x3932b4f2,0x361f3be7,0xb74438b4,0xb744bc00,0x3be738b4,0xb9a834f2,0xbb640000,0x361fb9a8,0x361f3c00,0xbb64b9a8,
0xbb9cb8b4,0x3b9c0000,0xb8b438b4,0xbb9c,0xb82ebb9c,0x3ad239a8,0xbbfab4f2,0x3b64b102,0x3102bb9c,0x31023c00,0xb744bb9c,0x39a83a79,0x3a15b8b4,0xb93239a8,0x382eba79,0xb61f3b21,
0x3c000000,0xbc000000,0x3c000000,0xbc000000,0x3a1538b4,0xb932b9a8,0x382e3a79,0xb61fbb21,0x31023b9c,0x3102bc00,0xb7443b9c,0x39a8ba79,0xb82e3b9c,0x3ad2b9a8,0xbbfa34f2,0x3b643102,
0xbb9c38b4,0x3b9c0000,0xb8b4b8b4,0x3b9c,0xbb640000,0x361f39a8,0x361fbc00,0xbb6439a8,0xb744b8b4,0xb7443c00,0x3be7b8b4,0xb9a8b4f2,0x3378bb9c,0xbbc739a8,0x393234f2,0x361fbbe7,
0x3a79bb9c,0xba790000,0xb4f23b9c,0x3c00b8b4,0x3bfab8b4,0xad05b9a8,0xbbc73a79,0x361f3744,0x39a80000,0x39a8bc00,0xb9a80000,0xb9a83c00,0x2d0538b4,0x3bfab9a8,0x3378ba79,0xbb643744,
0xb8b43b9c,0x38b40000,0x3b9cbb9c,0xb8b4,0xbbc73b9c,0xb37839a8,0x3a15b4f2,0x3b64bbe7,0xbb2138b4,0xbb213c00,0xb10238b4,0x39a8b4f2,0xb61f0000,0xbb6439a8,0xbb643c00,0xb61f39a8,
0x34f2b8b4,0xb4f20000,0xba7938b4,0xbc003b9c,0x3ad2bb9c,0x382eb9a8,0x2d05b4f2,0xb61f3102,0x3be7bb9c,0x3be7bc00,0x3b21bb9c,0x39a8ba79,0x3932b8b4,0x3a15b9a8,0x3ad2ba79,0x3b64bb21,
0x0,0x0,0x0,0x0,0xb93238b4,0xba1539a8,0xbad23a79,0xbb643b21,0xbbe73b9c,0xbbe73c00,0xbb213b9c,0xb9a83a79,0xbad23b9c,0xb82e39a8,0xad0534f2,0x361fb102,
0xb4f238b4,0x34f20000,0x3a79b8b4,0x3c00bb9c,0x361f0000,0x3b64b9a8,0x3b64bc00,0x361fb9a8,0x3b21b8b4,0x3b21bc00,0x3102b8b4,0xb9a834f2,0x3bc7bb9c,0x3378b9a8,0xba1534f2,0xbb643be7,
0x38b4bb9c,0xb8b40000,0xbb9c3b9c,0x38b4,0xad05b8b4,0xbbfa39a8,0xb3783a79,0x3b64b744,0xb9a80000,0xb9a83c00,0x39a80000,0x39a8bc00,0xbbfa38b4,0x2d0539a8,0x3bc7ba79,0xb61fb744,
0xba793b9c,0x3a790000,0x34f2bb9c,0xbc0038b4,0xb3783b9c,0x3bc7b9a8,0xb932b4f2,0xb61f3be7,0x374438b4,0x3744bc00,0xbbe738b4,0x39a834f2,0x3b640000,0xb61fb9a8,0xb61f3c00,0x3b64b9a8,
0x3b9cb8b4,0xbb9c0000,0x38b438b4,0xbb9c,0x382ebb9c,0xbad239a8,0x3bfab4f2,0xbb64b102,0xb102bb9c,0xb1023c00,0x3744bb9c,0xb9a83a79,0xba15b8b4,0x393239a8,0xb82eba79,0x361f3b21,
0xbc000000,0x3c000000,0xbc000000,0x3c000000,0xba1538b4,0x3932b9a8,0xb82e3a79,0x361fbb21,0xb1023b9c,0xb102bc00,0x37443b9c,0xb9a8ba79,0x382e3b9c,0xbad2b9a8,0x3bfa34f2,0xbb643102,
0x3b9c38b4,0xbb9c0000,0x38b4b8b4,0x3b9c,0x3b640000,0xb61f39a8,0xb61fbc00,0x3b6439a8,0x3744b8b4,0x37443c00,0xbbe7b8b4,0x39a8b4f2,0xb378bb9c,0x3bc739a8,0xb93234f2,0xb61fbbe7,
0xba79bb9c,0x3a790000,0x34f23b9c,0xbc00b8b4,0xbbfab8b4,0x2d05b9a8,0x3bc73a79,0xb61f3744,0xb9a80000,0xb9a8bc00,0x39a80000,0x39a83c00,0xad0538b4,0xbbfab9a8,0xb378ba79,0x3b643744,
0x38b43b9c,0xb8b40000,0xbb9cbb9c,0xb8b4,0x3bc73b9c,0x337839a8,0xba15b4f2,0xbb64bbe7,0x3b2138b4,0x3b213c00,0x310238b4,0xb9a8b4f2,0x361f0000,0x3b6439a8,0x3b643c00,0x361f39a8,
0xb4f2b8b4,0x34f20000,0x3a7938b4,0x3c003b9c,0xbad2bb9c,0xb82eb9a8,0xad05b4f2,0x361f3102,0xbbe7bb9c,0xbbe7bc00,0xbb21bb9c,0xb9a8ba79,0xb932b8b4,0xba15b9a8,0xbad2ba79,0xbb64bb21,
0x0,0x0,0x0,0x0,0x3bc73b9c,0x3bfa3be7,0x3bfa3c00,0x3bc73be7,0x374438b4,0x310234f2,0xb1020000,0xb744b4f2,0xba15b8b4,0xbbc7bb21,0xbbc7bc00,0xba15bb21,
0xba79bb9c,0xb4f2b8b4,0x34f20000,0x3a7938b4,0x361f0000,0x3b6439a8,0x3b643c00,0x361f39a8,0x3be73b9c,0x37443a79,0xb7440000,0xbbe7ba79,0x2d0538b4,0xbad2b744,0xbad2bc00,0x2d05b744,
0xbb9cb8b4,0xb8b4bb9c,0x38b40000,0x3b9c3b9c,0xb82ebb9c,0x3a153102,0x3a153c00,0xb82e3102,0x39a80000,0x39a83c00,0xb9a80000,0xb9a8bc00,0x3ad23b9c,0xb9323102,0xb932bc00,0x3ad23102,
0xb4f238b4,0xba79bb9c,0x3a790000,0x34f23b9c,0xbbfab8b4,0x382eb744,0x382e3c00,0xbbfab744,0xb102bb9c,0x3b213a79,0xbb210000,0x3102ba79,0x3b640000,0xb61f39a8,0xb61fbc00,0x3b6439a8,
0x38b43b9c,0xbb9cb8b4,0x3b9c0000,0xb8b438b4,0xb93238b4,0x3378bb21,0x33783c00,0xb932bb21,0xbb21b8b4,0x3be734f2,0xbbe70000,0x3b21b4f2,0x3378bb9c,0xad053be7,0xad05bc00,0x33783be7,
0x3c000000,0xbc000000,0x3c000000,0xbc000000,0x33783b9c,0xad05bbe7,0xad053c00,0x3378bbe7,0xbb2138b4,0x3be7b4f2,0xbbe70000,0x3b2134f2,0xb932b8b4,0x33783b21,0x3378bc00,0xb9323b21,
0x38b4bb9c,0xbb9c38b4,0x3b9c0000,0xb8b4b8b4,0x3b640000,0xb61fb9a8,0xb61f3c00,0x3b64b9a8,0xb1023b9c,0x3b21ba79,0xbb210000,0x31023a79,0xbbfa38b4,0x382e3744,0x382ebc00,0xbbfa3744,
0xb4f2b8b4,0xba793b9c,0x3a790000,0x34f2bb9c,0x3ad2bb9c,0xb932b102,0xb9323c00,0x3ad2b102,0x39a80000,0x39a8bc00,0xb9a80000,0xb9a83c00,0xb82e3b9c,0x3a15b102,0x3a15bc00,0xb82eb102,
0xbb9c38b4,0xb8b43b9c,0x38b40000,0x3b9cbb9c,0x2d05b8b4,0xbad23744,0xbad23c00,0x2d053744,0x3be7bb9c,0x3744ba79,0xb7440000,0xbbe73a79,0x361f0000,0x3b64b9a8,0x3b64bc00,0x361fb9a8,
0xba793b9c,0xb4f238b4,0x34f20000,0x3a79b8b4,0xba1538b4,0xbbc73b21,0xbbc73c00,0xba153b21,0x3744b8b4,0x3102b4f2,0xb1020000,0xb74434f2,0x3bc7bb9c,0x3bfabbe7,0x3bfabc00,0x3bc7bbe7,
0x0,0x0,0x0,0x0,0xbbc73b9c,0xbbfa3be7,0xbbfa3c00,0xbbc73be7,0xb74438b4,0xb10234f2,0x31020000,0x3744b4f2,0x3a15b8b4,0x3bc7bb21,0x3bc7bc00,0x3a15bb21,
0x3a79bb9c,0x34f2b8b4,0xb4f20000,0xba7938b4,0xb61f0000,0xbb6439a8,0xbb643c00,0xb61f39a8,0xbbe73b9c,0xb7443a79,0x37440000,0x3be7ba79,0xad0538b4,0x3ad2b744,0x3ad2bc00,0xad05b744,
0x3b9cb8b4,0x38b4bb9c,0xb8b40000,0xbb9c3b9c,0x382ebb9c,0xba153102,0xba153c00,0x382e3102,0xb9a80000,0xb9a83c00,0x39a80000,0x39a8bc00,0xbad23b9c,0x39323102,0x3932bc00,0xbad23102,
0x34f238b4,0x3a79bb9c,0xba790000,0xb4f23b9c,0x3bfab8b4,0xb82eb744,0xb82e3c00,0x3bfab744,0x3102bb9c,0xbb213a79,0x3b210000,0xb102ba79,0xbb640000,0x361f39a8,0x361fbc00,0xbb6439a8,
0xb8b43b9c,0x3b9cb8b4,0xbb9c0000,0x38b438b4,0x393238b4,0xb378bb21,0xb3783c00,0x3932bb21,0x3b21b8b4,0xbbe734f2,0x3be70000,0xbb21b4f2,0xb378bb9c,0x2d053be7,0x2d05bc00,0xb3783be7,
0xbc000000,0x3c000000,0xbc000000,0x3c000000,0xb3783b9c,0x2d05bbe7,0x2d053c00,0xb378bbe7,0x3b2138b4,0xbbe7b4f2,0x3be70000,0xbb2134f2,0x3932b8b4,0xb3783b21,0xb378bc00,0x39323b21,
0xb8b4bb9c,0x3b9c38b4,0xbb9c0000,0x38b4b8b4,0xbb640000,0x361fb9a8,0x361f3c00,0xbb64b9a8,0x31023b9c,0xbb21ba79,0x3b210000,0xb1023a79,0x3bfa38b4,0xb82e3744,0xb82ebc00,0x3bfa3744,
0x34f2b8b4,0x3a793b9c,0xba790000,0xb4f2bb9c,0xbad2bb9c,0x3932b102,0x39323c00,0xbad2b102,0xb9a80000,0xb9a8bc00,0x39a80000,0x39a83c00,0x382e3b9c,0xba15b102,0xba15bc00,0x382eb102,
0x3b9c38b4,0x38b43b9c,0xb8b40000,0xbb9cbb9c,0xad05b8b4,0x3ad23744,0x3ad23c00,0xad053744,0xbbe7bb9c,0xb744ba79,0x37440000,0x3be73a79,0xb61f0000,0xbb64b9a8,0xbb64bc00,0xb61fb9a8,
0x3a793b9c,0x34f238b4,0xb4f20000,0xba79b8b4,0x3a1538b4,0x3bc73b21,0x3bc73c00,0x3a153b21,0xb744b8b4,0xb102b4f2,0x31020000,0x374434f2,0xbbc7bb9c,0xbbfabbe7,0xbbfabc00,0xbbc7bbe7,
0x0,0x0,0x0,0x0,0x3b643b9c,0x3ad23b21,0x3a153a79,0x393239a8,0xb9a8b8b4,0xbb21ba79,0xbbe7bb9c,0xbbe7bc00,0xb61fb8b4,0x2d05b102,0x382e34f2,0x3ad239a8,
0x3c003b9c,0x3a793b9c,0x34f238b4,0xb4f20000,0xb61f0000,0xbb64b9a8,0xbb64bc00,0xb61fb9a8,0xb9a8bb9c,0x3102b4f2,0x3b2138b4,0x3b213c00,0x3b6438b4,0x3a153be7,0xb37834f2,0xbbc7b9a8,
0x38b4,0xbb9cb8b4,0xb8b4bb9c,0x38b40000,0xbb64bb9c,0x3378b744,0x3bfa3a79,0x2d0539a8,0x39a80000,0x39a83c00,0xb9a80000,0xb9a8bc00,0x361f3b9c,0xbbc7b744,0xad05ba79,0x3bfa39a8,
0xbc00b8b4,0x34f2b8b4,0x3a793b9c,0xba790000,0x361fb8b4,0x39323be7,0xbbc7b4f2,0x3378b9a8,0x39a83b9c,0xbbe7b4f2,0x3744b8b4,0x37443c00,0xbb640000,0x361fb9a8,0x361f3c00,0xbb64b9a8,
0xbb9c,0x38b43b9c,0xbb9cb8b4,0x3b9c0000,0x3b6438b4,0xbbfab102,0x3ad2b4f2,0xb82e39a8,0xb9a838b4,0x3744ba79,0xb1023b9c,0xb102bc00,0xb61fbb9c,0x382e3b21,0xb932ba79,0x3a1539a8,
0x3c000000,0xbc000000,0x3c000000,0xbc000000,0xb61f3b9c,0x382ebb21,0xb9323a79,0x3a15b9a8,0xb9a8b8b4,0x37443a79,0xb102bb9c,0xb1023c00,0x3b64b8b4,0xbbfa3102,0x3ad234f2,0xb82eb9a8,
0x3b9c,0x38b4bb9c,0xbb9c38b4,0x3b9c0000,0xbb640000,0x361f39a8,0x361fbc00,0xbb6439a8,0x39a8bb9c,0xbbe734f2,0x374438b4,0x3744bc00,0x361f38b4,0x3932bbe7,0xbbc734f2,0x337839a8,
0xbc0038b4,0x34f238b4,0x3a79bb9c,0xba790000,0x361fbb9c,0xbbc73744,0xad053a79,0x3bfab9a8,0x39a80000,0x39a8bc00,0xb9a80000,0xb9a83c00,0xbb643b9c,0x33783744,0x3bfaba79,0x2d05b9a8,
0xb8b4,0xbb9c38b4,0xb8b43b9c,0x38b40000,0x3b64b8b4,0x3a15bbe7,0xb378b4f2,0xbbc739a8,0xb9a83b9c,0x310234f2,0x3b21b8b4,0x3b21bc00,0xb61f0000,0xbb6439a8,0xbb643c00,0xb61f39a8,
0x3c00bb9c,0x3a79bb9c,0x34f2b8b4,0xb4f20000,0xb61f38b4,0x2d053102,0x382eb4f2,0x3ad2b9a8,0xb9a838b4,0xbb213a79,0xbbe73b9c,0xbbe73c00,0x3b64bb9c,0x3ad2bb21,0x3a15ba79,0x3932b9a8,
0x0,0x0,0x0,0x0,0xbb643b9c,0xbad23b21,0xba153a79,0xb93239a8,0x39a8b8b4,0x3b21ba79,0x3be7bb9c,0x3be7bc00,0x361fb8b4,0xad05b102,0xb82e34f2,0xbad239a8,
0xbc003b9c,0xba793b9c,0xb4f238b4,0x34f20000,0x361f0000,0x3b64b9a8,0x3b64bc00,0x361fb9a8,0x39a8bb9c,0xb102b4f2,0xbb2138b4,0xbb213c00,0xbb6438b4,0xba153be7,0x337834f2,0x3bc7b9a8,
0x38b4,0x3b9cb8b4,0x38b4bb9c,0xb8b40000,0x3b64bb9c,0xb378b744,0xbbfa3a79,0xad0539a8,0xb9a80000,0xb9a83c00,0x39a80000,0x39a8bc00,0xb61f3b9c,0x3bc7b744,0x2d05ba79,0xbbfa39a8,
0x3c00b8b4,0xb4f2b8b4,0xba793b9c,0x3a790000,0xb61fb8b4,0xb9323be7,0x3bc7b4f2,0xb378b9a8,0xb9a83b9c,0x3be7b4f2,0xb744b8b4,0xb7443c00,0x3b640000,0xb61fb9a8,0xb61f3c00,0x3b64b9a8,
0xbb9c,0xb8b43b9c,0x3b9cb8b4,0xbb9c0000,0xbb6438b4,0x3bfab102,0xbad2b4f2,0x382e39a8,0x39a838b4,0xb744ba79,0x31023b9c,0x3102bc00,0x361fbb9c,0xb82e3b21,0x3932ba79,0xba1539a8,
0xbc000000,0x3c000000,0xbc000000,0x3c000000,0x361f3b9c,0xb82ebb21,0x39323a79,0xba15b9a8,0x39a8b8b4,0xb7443a79,0x3102bb9c,0x31023c00,0xbb64b8b4,0x3bfa3102,0xbad234f2,0x382eb9a8,
0x3b9c,0xb8b4bb9c,0x3b9c38b4,0xbb9c0000,0x3b640000,0xb61f39a8,0xb61fbc00,0x3b6439a8,0xb9a8bb9c,0x3be734f2,0xb74438b4,0xb744bc00,0xb61f38b4,0xb932bbe7,0x3bc734f2,0xb37839a8,
0x3c0038b4,0xb4f238b4,0xba79bb9c,0x3a790000,0xb61fbb9c,0x3bc73744,0x2d053a79,0xbbfab9a8,0xb9a80000,0xb9a8bc00,0x39a80000,0x39a83c00,0x3b643b9c,0xb3783744,0xbbfaba79,0xad05b9a8,
0xb8b4,0x3b9c38b4,0x38b43b9c,0xb8b40000,0xbb64b8b4,0xba15bbe7,0x3378b4f2,0x3bc739a8,0x39a83b9c,0xb10234f2,0xbb21b8b4,0xbb21bc00,0x361f0000,0x3b6439a8,0x3b643c00,0x361f39a8,
0xbc00bb9c,0xba79bb9c,0xb4f2b8b4,0x34f20000,0x361f38b4,0xad053102,0xb82eb4f2,0xbad2b9a8,0x39a838b4,0x3b213a79,0x3be73b9c,0x3be73c00,0xbb64bb9c,0xbad2bb21,0xba15ba79,0xb932b9a8,
0x0,0x0,0x0,0x0,0x382e38b4,0x361f3744,0x337834f2,0x2d053102,0xbb21bb9c,0xb9a8ba79,0xb744b8b4,0xb102b4f2,0x3bfa3b9c,0x3b643be7,0x39323a79,0x33783744,
0xba79b8b4,0xbc00bb9c,0xba79bb9c,0xb4f2b8b4,0x361f0000,0x3b6439a8,0x3b643c00,0x361f39a8,0x310238b4,0xb9a8b4f2,0xbbe7bb9c,0xb744ba79,0xb932bb9c,0x361fb102,0x3bfa3a79,0x382e3b21,
0x3b9c3b9c,0x38b4,0xbb9cb8b4,0xb8b4bb9c,0xbbc7b8b4,0xb61fbb21,0x3ad234f2,0x39323be7,0x39a80000,0x39a83c00,0xb9a80000,0xb9a8bc00,0xb37838b4,0xbb64bb21,0x382eb4f2,0x3a153be7,
0xb4f2bb9c,0x3c0038b4,0xb4f238b4,0xba79bb9c,0x3a153b9c,0xbb64b102,0x2d05ba79,0x3ad23b21,0xbbe7b8b4,0x39a8b4f2,0x31023b9c,0xbb21ba79,0x3b640000,0xb61f39a8,0xb61fbc00,0x3b6439a8,
0xb8b438b4,0xbb9c,0x38b43b9c,0xbb9cb8b4,0x2d05bb9c,0x361f3be7,0xba15ba79,0x3bc73744,0x37443b9c,0xb9a8ba79,0x3b2138b4,0xbbe7b4f2,0xbad2b8b4,0x3b643744,0xbbc7b4f2,0x3bfa3102,
0x3c000000,0xbc000000,0x3c000000,0xbc000000,0xbad238b4,0x3b64b744,0xbbc734f2,0x3bfab102,0x3744bb9c,0xb9a83a79,0x3b21b8b4,0xbbe734f2,0x2d053b9c,0x361fbbe7,0xba153a79,0x3bc7b744,
0xb8b4b8b4,0x3b9c,0x38b4bb9c,0xbb9c38b4,0x3b640000,0xb61fb9a8,0xb61f3c00,0x3b64b9a8,0xbbe738b4,0x39a834f2,0x3102bb9c,0xbb213a79,0x3a15bb9c,0xbb643102,0x2d053a79,0x3ad2bb21,
0xb4f23b9c,0x3c00b8b4,0xb4f2b8b4,0xba793b9c,0xb378b8b4,0xbb643b21,0x382e34f2,0x3a15bbe7,0x39a80000,0x39a8bc00,0xb9a80000,0xb9a83c00,0xbbc738b4,0xb61f3b21,0x3ad2b4f2,0x3932bbe7,
0x3b9cbb9c,0xb8b4,0xbb9c38b4,0xb8b43b9c,0xb9323b9c,0x361f3102,0x3bfaba79,0x382ebb21,0x3102b8b4,0xb9a834f2,0xbbe73b9c,0xb7443a79,0x361f0000,0x3b64b9a8,0x3b64bc00,0x361fb9a8,
0xba7938b4,0xbc003b9c,0xba793b9c,0xb4f238b4,0x3bfabb9c,0x3b64bbe7,0x3932ba79,0x3378b744,0xbb213b9c,0xb9a83a79,0xb74438b4,0xb10234f2,0x382eb8b4,0x361fb744,0x3378b4f2,0x2d05b102,
0x0,0x0,0x0,0x0,0xb82e38b4,0xb61f3744,0xb37834f2,0xad053102,0x3b21bb9c,0x39a8ba79,0x3744b8b4,0x3102b4f2,0xbbfa3b9c,0xbb643be7,0xb9323a79,0xb3783744,
0x3a79b8b4,0x3c00bb9c,0x3a79bb9c,0x34f2b8b4,0xb61f0000,0xbb6439a8,0xbb643c00,0xb61f39a8,0xb10238b4,0x39a8b4f2,0x3be7bb9c,0x3744ba79,0x3932bb9c,0xb61fb102,0xbbfa3a79,0xb82e3b21,
0xbb9c3b9c,0x38b4,0x3b9cb8b4,0x38b4bb9c,0x3bc7b8b4,0x361fbb21,0xbad234f2,0xb9323be7,0xb9a80000,0xb9a83c00,0x39a80000,0x39a8bc00,0x337838b4,0x3b64bb21,0xb82eb4f2,0xba153be7,
0x34f2bb9c,0xbc0038b4,0x34f238b4,0x3a79bb9c,0xba153b9c,0x3b64b102,0xad05ba79,0xbad23b21,0x3be7b8b4,0xb9a8b4f2,0xb1023b9c,0x3b21ba79,0xbb640000,0x361f39a8,0x361fbc00,0xbb6439a8,
0x38b438b4,0xbb9c,0xb8b43b9c,0x3b9cb8b4,0xad05bb9c,0xb61f3be7,0x3a15ba79,0xbbc73744,0xb7443b9c,0x39a8ba79,0xbb2138b4,0x3be7b4f2,0x3ad2b8b4,0xbb643744,0x3bc7b4f2,0xbbfa3102,
0xbc000000,0x3c000000,0xbc000000,0x3c000000,0x3ad238b4,0xbb64b744,0x3bc734f2,0xbbfab102,0xb744bb9c,0x39a83a79,0xbb21b8b4,0x3be734f2,0xad053b9c,0xb61fbbe7,0x3a153a79,0xbbc7b744,
0x38b4b8b4,0x3b9c,0xb8b4bb9c,0x3b9c38b4,0xbb640000,0x361fb9a8,0x361f3c00,0xbb64b9a8,0x3be738b4,0xb9a834f2,0xb102bb9c,0x3b213a79,0xba15bb9c,0x3b643102,0xad053a79,0xbad2bb21,
0x34f23b9c,0xbc00b8b4,0x34f2b8b4,0x3a793b9c,0x3378b8b4,0x3b643b21,0xb82e34f2,0xba15bbe7,0xb9a80000,0xb9a8bc00,0x39a80000,0x39a83c00,0x3bc738b4,0x361f3b21,0xbad2b4f2,0xb932bbe7,
0xbb9cbb9c,0xb8b4,0x3b9c38b4,0x38b43b9c,0x39323b9c,0xb61f3102,0xbbfaba79,0xb82ebb21,0xb102b8b4,0x39a834f2,0x3be73b9c,0x37443a79,0xb61f0000,0xbb64b9a8,0xbb64bc00,0xb61fb9a8,
0x3a7938b4,0x3c003b9c,0x3a793b9c,0x34f238b4,0xbbfabb9c,0xbb64bbe7,0xb932ba79,0xb378b744,0x3b213b9c,0x39a83a79,0x374438b4,0x310234f2,0xb82eb8b4,0xb61fb744,0xb378b4f2,0xad05b102,
0x0,0x0,0x0,0x0,0xad050000,0xb378b102,0xb61fb4f2,0xb82eb744,0x31020000,0x374434f2,0x39a838b4,0x3b213a79,0xb3780000,0xb932b744,0xbb64ba79,0xbbfabbe7,
0x34f20000,0x3a7938b4,0x3c003b9c,0x3a793b9c,0xb61f0000,0xbb64b9a8,0xbb64bc00,0xb61fb9a8,0x37440000,0x3be73a79,0x39a83b9c,0xb10234f2,0xb82e0000,0xbbfabb21,0xb61fba79,0x39323102,
0x38b40000,0x3b9c3b9c,0x38b4,0xbb9cb8b4,0xb9320000,0xbad2bbe7,0x361fb4f2,0x3bc73b21,0x39a80000,0x39a83c00,0xb9a80000,0xb9a8bc00,0xba150000,0xb82ebbe7,0x3b6434f2,0x33783b21,
0x3a790000,0x34f23b9c,0xbc00b8b4,0x34f2b8b4,0xbad20000,0xad05bb21,0x3b643a79,0xba153102,0x3b210000,0xb1023a79,0xb9a8bb9c,0x3be734f2,0xbb640000,0x361fb9a8,0x361f3c00,0xbb64b9a8,
0x3b9c0000,0xb8b438b4,0xbb9c,0x38b43b9c,0xbbc70000,0x3a15b744,0xb61f3a79,0xad05bbe7,0x3be70000,0xbb2134f2,0x39a8b8b4,0xb7443a79,0xbbfa0000,0x3bc7b102,0xbb6434f2,0x3ad2b744,
0x3c000000,0xbc000000,0x3c000000,0xbc000000,0xbbfa0000,0x3bc73102,0xbb64b4f2,0x3ad23744,0x3be70000,0xbb21b4f2,0x39a838b4,0xb744ba79,0xbbc70000,0x3a153744,0xb61fba79,0xad053be7,
0x3b9c0000,0xb8b4b8b4,0x3b9c,0x38b4bb9c,0xbb640000,0x361f39a8,0x361fbc00,0xbb6439a8,0x3b210000,0xb102ba79,0xb9a83b9c,0x3be7b4f2,0xbad20000,0xad053b21,0x3b64ba79,0xba15b102,
0x3a790000,0x34f2bb9c,0xbc0038b4,0x34f238b4,0xba150000,0xb82e3be7,0x3b64b4f2,0x3378bb21,0x39a80000,0x39a8bc00,0xb9a80000,0xb9a83c00,0xb9320000,0xbad23be7,0x361f34f2,0x3bc7bb21,
0x38b40000,0x3b9cbb9c,0xb8b4,0xbb9c38b4,0xb82e0000,0xbbfa3b21,0xb61f3a79,0x3932b102,0x37440000,0x3be7ba79,0x39a8bb9c,0xb102b4f2,0xb61f0000,0xbb6439a8,0xbb643c00,0xb61f39a8,
0x34f20000,0x3a79b8b4,0x3c00bb9c,0x3a79bb9c,0xb3780000,0xb9323744,0xbb643a79,0xbbfa3be7,0x31020000,0x3744b4f2,0x39a8b8b4,0x3b21ba79,0xad050000,0xb3783102,0xb61f34f2,0xb82e3744,
0x0,0x0,0x0,0x0,0x2d050000,0x3378b102,0x361fb4f2,0x382eb744,0xb1020000,0xb74434f2,0xb9a838b4,0xbb213a79,0x33780000,0x3932b744,0x3b64ba79,0x3bfabbe7,
0xb4f20000,0xba7938b4,0xbc003b9c,0xba793b9c,0x361f0000,0x3b64b9a8,0x3b64bc00,0x361fb9a8,0xb7440000,0xbbe73a79,0xb9a83b9c,0x310234f2,0x382e0000,0x3bfabb21,0x361fba79,0xb9323102,
0xb8b40000,0xbb9c3b9c,0x38b4,0x3b9cb8b4,0x39320000,0x3ad2bbe7,0xb61fb4f2,0xbbc73b21,0xb9a80000,0xb9a83c00,0x39a80000,0x39a8bc00,0x3a150000,0x382ebbe7,0xbb6434f2,0xb3783b21,
0xba790000,0xb4f23b9c,0x3c00b8b4,0xb4f2b8b4,0x3ad20000,0x2d05bb21,0xbb643a79,0x3a153102,0xbb210000,0x31023a79,0x39a8bb9c,0xbbe734f2,0x3b640000,0xb61fb9a8,0xb61f3c00,0x3b64b9a8,
0xbb9c0000,0x38b438b4,0xbb9c,0xb8b43b9c,0x3bc70000,0xba15b744,0x361f3a79,0x2d05bbe7,0xbbe70000,0x3b2134f2,0xb9a8b8b4,0x37443a79,0x3bfa0000,0xbbc7b102,0x3b6434f2,0xbad2b744,
0xbc000000,0x3c000000,0xbc000000,0x3c000000,0x3bfa0000,0xbbc73102,0x3b64b4f2,0xbad23744,0xbbe70000,0x3b21b4f2,0xb9a838b4,0x3744ba79,0x3bc70000,0xba153744,0x361fba79,0x2d053be7,
0xbb9c0000,0x38b4b8b4,0x3b9c,0xb8b4bb9c,0x3b640000,0xb61f39a8,0xb61fbc00,0x3b6439a8,0xbb210000,0x3102ba79,0x39a83b9c,0xbbe7b4f2,0x3ad20000,0x2d053b21,0xbb64ba79,0x3a15b102,
0xba790000,0xb4f2bb9c,0x3c0038b4,0xb4f238b4,0x3a150000,0x382e3be7,0xbb64b4f2,0xb378bb21,0xb9a80000,0xb9a8bc00,0x39a80000,0x39a83c00,0x39320000,0x3ad23be7,0xb61f34f2,0xbbc7bb21,
0xb8b40000,0xbb9cbb9c,0xb8b4,0x3b9c38b4,0x382e0000,0x3bfa3b21,0x361f3a79,0xb932b102,0xb7440000,0xbbe7ba79,0xb9a8bb9c,0x3102b4f2,0x361f0000,0x3b6439a8,0x3b643c00,0x361f39a8,
0xb4f20000,0xba79b8b4,0xbc00bb9c,0xba79bb9c,0x33780000,0x39323744,0x3b643a79,0x3bfa3be7,0xb1020000,0xb744b4f2,0xb9a8b8b4,0xbb21ba79,0x2d050000,0x33783102,0x361f34f2,0x382e3744,
0x0,0x0,0x0,0x0,0xb932b8b4,0xba15b9a8,0xbad2ba79,0xbb64bb21,0x3be73b9c,0x3be73c00,0x3b213b9c,0x39a83a79,0xbad2bb9c,0xb82eb9a8,0xad05b4f2,0x361f3102,
0x34f238b4,0xb4f20000,0xba79b8b4,0xbc00bb9c,0x361f0000,0x3b6439a8,0x3b643c00,0x361f39a8,0xbb21b8b4,0xbb21bc00,0xb102b8b4,0x39a834f2,0x3bc73b9c,0x337839a8,0xba15b4f2,0xbb64bbe7,
0xb8b4bb9c,0x38b40000,0x3b9c3b9c,0x38b4,0xad0538b4,0xbbfab9a8,0xb378ba79,0x3b643744,0x39a80000,0x39a83c00,0xb9a80000,0xb9a8bc00,0xbbfab8b4,0x2d05b9a8,0x3bc73a79,0xb61f3744,
0x3a793b9c,0xba790000,0xb4f2bb9c,0x3c0038b4,0xb378bb9c,0x3bc739a8,0xb93234f2,0xb61fbbe7,0xb74438b4,0xb744bc00,0x3be738b4,0xb9a834f2,0x3b640000,0xb61f39a8,0xb61fbc00,0x3b6439a8,
0xbb9cb8b4,0x3b9c0000,0xb8b438b4,0xbb9c,0x382e3b9c,0xbad2b9a8,0x3bfa34f2,0xbb643102,0x3102bb9c,0x31023c00,0xb744bb9c,0x39a83a79,0xba1538b4,0x3932b9a8,0xb82e3a79,0x361fbb21,
0x3c000000,0xbc000000,0x3c000000,0xbc000000,0xba15b8b4,0x393239a8,0xb82eba79,0x361f3b21,0x31023b9c,0x3102bc00,0xb7443b9c,0x39a8ba79,0x382ebb9c,0xbad239a8,0x3bfab4f2,0xbb64b102,
0xbb9c38b4,0x3b9c0000,0xb8b4b8b4,0x3b9c,0x3b640000,0xb61fb9a8,0xb61f3c00,0x3b64b9a8,0xb744b8b4,0xb7443c00,0x3be7b8b4,0xb9a8b4f2,0xb3783b9c,0x3bc7b9a8,0xb932b4f2,0xb61f3be7,
0x3a79bb9c,0xba790000,0xb4f23b9c,0x3c00b8b4,0xbbfa38b4,0x2d0539a8,0x3bc7ba79,0xb61fb744,0x39a80000,0x39a8bc00,0xb9a80000,0xb9a83c00,0xad05b8b4,0xbbfa39a8,0xb3783a79,0x3b64b744,
0xb8b43b9c,0x38b40000,0x3b9cbb9c,0xb8b4,0x3bc7bb9c,0x3378b9a8,0xba1534f2,0xbb643be7,0xbb2138b4,0xbb213c00,0xb10238b4,0x39a8b4f2,0x361f0000,0x3b64b9a8,0x3b64bc00,0x361fb9a8,
0x34f2b8b4,0xb4f20000,0xba7938b4,0xbc003b9c,0xbad23b9c,0xb82e39a8,0xad0534f2,0x361fb102,0x3be7bb9c,0x3be7bc00,0x3b21bb9c,0x39a8ba79,0xb93238b4,0xba1539a8,0xbad23a79,0xbb643b21,
0x0,0x0,0x0,0x0,0x3932b8b4,0x3a15b9a8,0x3ad2ba79,0x3b64bb21,0xbbe73b9c,0xbbe73c00,0xbb213b9c,0xb9a83a79,0x3ad2bb9c,0x382eb9a8,0x2d05b4f2,0xb61f3102,
0xb4f238b4,0x34f20000,0x3a79b8b4,0x3c00bb9c,0xb61f0000,0xbb6439a8,0xbb643c00,0xb61f39a8,0x3b21b8b4,0x3b21bc00,0x3102b8b4,0xb9a834f2,0xbbc73b9c,0xb37839a8,0x3a15b4f2,0x3b64bbe7,
0x38b4bb9c,0xb8b40000,0xbb9c3b9c,0x38b4,0x2d0538b4,0x3bfab9a8,0x3378ba79,0xbb643744,0xb9a80000,0xb9a83c00,0x39a80000,0x39a8bc00,0x3bfab8b4,0xad05b9a8,0xbbc73a79,0x361f3744,
0xba793b9c,0x3a790000,0x34f2bb9c,0xbc0038b4,0x3378bb9c,0xbbc739a8,0x393234f2,0x361fbbe7,0x374438b4,0x3744bc00,0xbbe738b4,0x39a834f2,0xbb640000,0x361f39a8,0x361fbc00,0xbb6439a8,
0x3b9cb8b4,0xbb9c0000,0x38b438b4,0xbb9c,0xb82e3b9c,0x3ad2b9a8,0xbbfa34f2,0x3b643102,0xb102bb9c,0xb1023c00,0x3744bb9c,0xb9a83a79,0x3a1538b4,0xb932b9a8,0x382e3a79,0xb61fbb21,
0xbc000000,0x3c000000,0xbc000000,0x3c000000,0x3a15b8b4,0xb93239a8,0x382eba79,0xb61f3b21,0xb1023b9c,0xb102bc00,0x37443b9c,0xb9a8ba79,0xb82ebb9c,0x3ad239a8,0xbbfab4f2,0x3b64b102,
0x3b9c38b4,0xbb9c0000,0x38b4b8b4,0x3b9c,0xbb640000,0x361fb9a8,0x361f3c00,0xbb64b9a8,0x3744b8b4,0x37443c00,0xbbe7b8b4,0x39a8b4f2,0x33783b9c,0xbbc7b9a8,0x3932b4f2,0x361f3be7,
0xba79bb9c,0x3a790000,0x34f23b9c,0xbc00b8b4,0x3bfa38b4,0xad0539a8,0xbbc7ba79,0x361fb744,0xb9a80000,0xb9a8bc00,0x39a80000,0x39a83c00,0x2d05b8b4,0x3bfa39a8,0x33783a79,0xbb64b744,
0x38b43b9c,0xb8b40000,0xbb9cbb9c,0xb8b4,0xbbc7bb9c,0xb378b9a8,0x3a1534f2,0x3b643be7,0x3b2138b4,0x3b213c00,0x310238b4,0xb9a8b4f2,0xb61f0000,0xbb64b9a8,0xbb64bc00,0xb61fb9a8,
0xb4f2b8b4,0x34f20000,0x3a7938b4,0x3c003b9c,0x3ad23b9c,0x382e39a8,0x2d0534f2,0xb61fb102,0xbbe7bb9c,0xbbe7bc00,0xbb21bb9c,0xb9a8ba79,0x393238b4,0x3a1539a8,0x3ad23a79,0x3b643b21,
0x0,0x0,0x0,0x0,0xbbc7bb9c,0xbbfabbe7,0xbbfabc00,0xbbc7bbe7,0x374438b4,0x310234f2,0xb1020000,0xb744b4f2,0x3a1538b4,0x3bc73b21,0x3bc73c00,0x3a153b21,
0xba79bb9c,0xb4f2b8b4,0x34f20000,0x3a7938b4,0xb61f0000,0xbb64b9a8,0xbb64bc00,0xb61fb9a8,0x3be73b9c,0x37443a79,0xb7440000,0xbbe7ba79,0xad05b8b4,0x3ad23744,0x3ad23c00,0xad053744,
0xbb9cb8b4,0xb8b4bb9c,0x38b40000,0x3b9c3b9c,0x382e3b9c,0xba15b102,0xba15bc00,0x382eb102,0x39a80000,0x39a83c00,0xb9a80000,0xb9a8bc00,0xbad2bb9c,0x3932b102,0x39323c00,0xbad2b102,
0xb4f238b4,0xba79bb9c,0x3a790000,0x34f23b9c,0x3bfa38b4,0xb82e3744,0xb82ebc00,0x3bfa3744,0xb102bb9c,0x3b213a79,0xbb210000,0x3102ba79,0xbb640000,0x361fb9a8,0x361f3c00,0xbb64b9a8,
0x38b43b9c,0xbb9cb8b4,0x3b9c0000,0xb8b438b4,0x3932b8b4,0xb3783b21,0xb378bc00,0x39323b21,0xbb21b8b4,0x3be734f2,0xbbe70000,0x3b21b4f2,0xb3783b9c,0x2d05bbe7,0x2d053c00,0xb378bbe7,
0x3c000000,0xbc000000,0x3c000000,0xbc000000,0xb378bb9c,0x2d053be7,0x2d05bc00,0xb3783be7,0xbb2138b4,0x3be7b4f2,0xbbe70000,0x3b2134f2,0x393238b4,0xb378bb21,0xb3783c00,0x3932bb21,
0x38b4bb9c,0xbb9c38b4,0x3b9c0000,0xb8b4b8b4,0xbb640000,0x361f39a8,0x361fbc00,0xbb6439a8,0xb1023b9c,0x3b21ba79,0xbb210000,0x31023a79,0x3bfab8b4,0xb82eb744,0xb82e3c00,0x3bfab744,
0xb4f2b8b4,0xba793b9c,0x3a790000,0x34f2bb9c,0xbad23b9c,0x39323102,0x3932bc00,0xbad23102,0x39a80000,0x39a8bc00,0xb9a80000,0xb9a83c00,0x382ebb9c,0xba153102,0xba153c00,0x382e3102,
0xbb9c38b4,0xb8b43b9c,0x38b40000,0x3b9cbb9c,0xad0538b4,0x3ad2b744,0x3ad2bc00,0xad05b744,0x3be7bb9c,0x3744ba79,0xb7440000,0xbbe73a79,0xb61f0000,0xbb6439a8,0xbb643c00,0xb61f39a8,
0xba793b9c,0xb4f238b4,0x34f20000,0x3a79b8b4,0x3a15b8b4,0x3bc7bb21,0x3bc7bc00,0x3a15bb21,0x3744b8b4,0x3102b4f2,0xb1020000,0xb74434f2,0xbbc73b9c,0xbbfa3be7,0xbbfa3c00,0xbbc73be7,
0x0,0x0,0x0,0x0,0x3bc7bb9c,0x3bfabbe7,0x3bfabc00,0x3bc7bbe7,0xb74438b4,0xb10234f2,0x31020000,0x3744b4f2,0xba1538b4,0xbbc73b21,0xbbc73c00,0xba153b21,
0x3a79bb9c,0x34f2b8b4,0xb4f20000,0xba7938b4,0x361f0000,0x3b64b9a8,0x3b64bc00,0x361fb9a8,0xbbe73b9c,0xb7443a79,0x37440000,0x3be7ba79,0x2d05b8b4,0xbad23744,0xbad23c00,0x2d053744,
0x3b9cb8b4,0x38b4bb9c,0xb8b40000,0xbb9c3b9c,0xb82e3b9c,0x3a15b102,0x3a15bc00,0xb82eb102,0xb9a80000,0xb9a83c00,0x39a80000,0x39a8bc00,0x3ad2bb9c,0xb932b102,0xb9323c00,0x3ad2b102,
0x34f238b4,0x3a79bb9c,0xba790000,0xb4f23b9c,0xbbfa38b4,0x382e3744,0x382ebc00,0xbbfa3744,0x3102bb9c,0xbb213a79,0x3b210000,0xb102ba79,0x3b640000,0xb61fb9a8,0xb61f3c00,0x3b64b9a8,
0xb8b43b9c,0x3b9cb8b4,0xbb9c0000,0x38b438b4,0xb932b8b4,0x33783b21,0x3378bc00,0xb9323b21,0x3b21b8b4,0xbbe734f2,0x3be70000,0xbb21b4f2,0x33783b9c,0xad05bbe7,0xad053c00,0x3378bbe7,
0xbc000000,0x3c000000,0xbc000000,0x3c000000,0x3378bb9c,0xad053be7,0xad05bc00,0x33783be7,0x3b2138b4,0xbbe7b4f2,0x3be70000,0xbb2134f2,0xb93238b4,0x3378bb21,0x33783c00,0xb932bb21,
0xb8b4bb9c,0x3b9c38b4,0xbb9c0000,0x38b4b8b4,0x3b640000,0xb61f39a8,0xb61fbc00,0x3b6439a8,0x31023b9c,0xbb21ba79,0x3b210000,0xb1023a79,0xbbfab8b4,0x382eb744,0x382e3c00,0xbbfab744,
0x34f2b8b4,0x3a793b9c,0xba790000,0xb4f2bb9c,0x3ad23b9c,0xb9323102,0xb932bc00,0x3ad23102,0xb9a80000,0xb9a8bc00,0x39a80000,0x39a83c00,0xb82ebb9c,0x3a153102,0x3a153c00,0xb82e3102,
0x3b9c38b4,0x38b43b9c,0xb8b40000,0xbb9cbb9c,0x2d0538b4,0xbad2b744,0xbad2bc00,0x2d05b744,0xbbe7bb9c,0xb744ba79,0x37440000,0x3be73a79,0x361f0000,0x3b6439a8,0x3b643c00,0x361f39a8,
0x3a793b9c,0x34f238b4,0xb4f20000,0xba79b8b4,0xba15b8b4,0xbbc7bb21,0xbbc7bc00,0xba15bb21,0xb744b8b4,0xb102b4f2,0x31020000,0x374434f2,0x3bc73b9c,0x3bfa3be7,0x3bfa3c00,0x3bc73be7,
0x0,0x0,0x0,0x0,0xbb64bb9c,0xbad2bb21,0xba15ba79,0xb932b9a8,0xb9a8b8b4,0xbb21ba79,0xbbe7bb9c,0xbbe7bc00,0x361f38b4,0xad053102,0xb82eb4f2,0xbad2b9a8,
0x3c003b9c,0x3a793b9c,0x34f238b4,0xb4f20000,0x361f0000,0x3b6439a8,0x3b643c00,0x361f39a8,0xb9a8bb9c,0x3102b4f2,0x3b2138b4,0x3b213c00,0xbb64b8b4,0xba15bbe7,0x3378b4f2,0x3bc739a8,
0x38b4,0xbb9cb8b4,0xb8b4bb9c,0x38b40000,0x3b643b9c,0xb3783744,0xbbfaba79,0xad05b9a8,0x39a80000,0x39a83c00,0xb9a80000,0xb9a8bc00,0xb61fbb9c,0x3bc73744,0x2d053a79,0xbbfab9a8,
0xbc00b8b4,0x34f2b8b4,0x3a793b9c,0xba790000,0xb61f38b4,0xb932bbe7,0x3bc734f2,0xb37839a8,0x39a83b9c,0xbbe7b4f2,0x3744b8b4,0x37443c00,0x3b640000,0xb61f39a8,0xb61fbc00,0x3b6439a8,
0xbb9c,0x38b43b9c,0xbb9cb8b4,0x3b9c0000,0xbb64b8b4,0x3bfa3102,0xbad234f2,0x382eb9a8,0xb9a838b4,0x3744ba79,0xb1023b9c,0xb102bc00,0x361f3b9c,0xb82ebb21,0x39323a79,0xba15b9a8,
0x3c000000,0xbc000000,0x3c000000,0xbc000000,0x361fbb9c,0xb82e3b21,0x3932ba79,0xba1539a8,0xb9a8b8b4,0x37443a79,0xb102bb9c,0xb1023c00,0xbb6438b4,0x3bfab102,0xbad2b4f2,0x382e39a8,
0x3b9c,0x38b4bb9c,0xbb9c38b4,0x3b9c0000,0x3b640000,0xb61fb9a8,0xb61f3c00,0x3b64b9a8,0x39a8bb9c,0xbbe734f2,0x374438b4,0x3744bc00,0xb61fb8b4,0xb9323be7,0x3bc7b4f2,0xb378b9a8,
0xbc0038b4,0x34f238b4,0x3a79bb9c,0xba790000,0xb61f3b9c,0x3bc7b744,0x2d05ba79,0xbbfa39a8,0x39a80000,0x39a8bc00,0xb9a80000,0xb9a83c00,0x3b64bb9c,0xb378b744,0xbbfa3a79,0xad0539a8,
0xb8b4,0xbb9c38b4,0xb8b43b9c,0x38b40000,0xbb6438b4,0xba153be7,0x337834f2,0x3bc7b9a8,0xb9a83b9c,0x310234f2,0x3b21b8b4,0x3b21bc00,0x361f0000,0x3b64b9a8,0x3b64bc00,0x361fb9a8,
0x3c00bb9c,0x3a79bb9c,0x34f2b8b4,0xb4f20000,0x361fb8b4,0xad05b102,0xb82e34f2,0xbad239a8,0xb9a838b4,0xbb213a79,0xbbe73b9c,0xbbe73c00,0xbb643b9c,0xbad23b21,0xba153a79,0xb93239a8,
0x0,0x0,0x0,0x0,0x3b64bb9c,0x3ad2bb21,0x3a15ba79,0x3932b9a8,0x39a8b8b4,0x3b21ba79,0x3be7bb9c,0x3be7bc00,0xb61f38b4,0x2d053102,0x382eb4f2,0x3ad2b9a8,
0xbc003b9c,0xba793b9c,0xb4f238b4,0x34f20000,0xb61f0000,0xbb6439a8,0xbb643c00,0xb61f39a8,0x39a8bb9c,0xb102b4f2,0xbb2138b4,0xbb213c00,0x3b64b8b4,0x3a15bbe7,0xb378b4f2,0xbbc739a8,
0x38b4,0x3b9cb8b4,0x38b4bb9c,0xb8b40000,0xbb643b9c,0x33783744,0x3bfaba79,0x2d05b9a8,0xb9a80000,0xb9a83c00,0x39a80000,0x39a8bc00,0x361fbb9c,0xbbc73744,0xad053a79,0x3bfab9a8,
0x3c00b8b4,0xb4f2b8b4,0xba793b9c,0x3a790000,0x361f38b4,0x3932bbe7,0xbbc734f2,0x337839a8,0xb9a83b9c,0x3be7b4f2,0xb744b8b4,0xb7443c00,0xbb640000,0x361f39a8,0x361fbc00,0xbb6439a8,
0xbb9c,0xb8b43b9c,0x3b9cb8b4,0xbb9c0000,0x3b64b8b4,0xbbfa3102,0x3ad234f2,0xb82eb9a8,0x39a838b4,0xb744ba79,0x31023b9c,0x3102bc00,0xb61f3b9c,0x382ebb21,0xb9323a79,0x3a15b9a8,
0xbc000000,0x3c000000,0xbc000000,0x3c000000,0xb61fbb9c,0x382e3b21,0xb932ba79,0x3a1539a8,0x39a8b8b4,0xb7443a79,0x3102bb9c,0x31023c00,0x3b6438b4,0xbbfab102,0x3ad2b4f2,0xb82e39a8,
0x3b9c,0xb8b4bb9c,0x3b9c38b4,0xbb9c0000,0xbb640000,0x361fb9a8,0x361f3c00,0xbb64b9a8,0xb9a8bb9c,0x3be734f2,0xb74438b4,0xb744bc00,0x361fb8b4,0x39323be7,0xbbc7b4f2,0x3378b9a8,
0x3c0038b4,0xb4f238b4,0xba79bb9c,0x3a790000,0x361f3b9c,0xbbc7b744,0xad05ba79,0x3bfa39a8,0xb9a80000,0xb9a8bc00,0x39a80000,0x39a83c00,0xbb64bb9c,0x3378b744,0x3bfa3a79,0x2d0539a8,
0xb8b4,0x3b9c38b4,0x38b43b9c,0xb8b40000,0x3b6438b4,0x3a153be7,0xb37834f2,0xbbc7b9a8,0x39a83b9c,0xb10234f2,0xbb21b8b4,0xbb21bc00,0xb61f0000,0xbb64b9a8,0xbb64bc00,0xb61fb9a8,
0xbc00bb9c,0xba79bb9c,0xb4f2b8b4,0x34f20000,0xb61fb8b4,0x2d05b102,0x382e34f2,0x3ad239a8,0x39a838b4,0x3b213a79,0x3be73b9c,0x3be73c00,0x3b643b9c,0x3ad23b21,0x3a153a79,0x393239a8,
0x0,0x0,0x0,0x0,0xb82eb8b4,0xb61fb744,0xb378b4f2,0xad05b102,0xbb21bb9c,0xb9a8ba79,0xb744b8b4,0xb102b4f2,0xbbfabb9c,0xbb64bbe7,0xb932ba79,0xb378b744,
0xba79b8b4,0xbc00bb9c,0xba79bb9c,0xb4f2b8b4,0xb61f0000,0xbb64b9a8,0xbb64bc00,0xb61fb9a8,0x310238b4,0xb9a8b4f2,0xbbe7bb9c,0xb744ba79,0x39323b9c,0xb61f3102,0xbbfaba79,0xb82ebb21,
0x3b9c3b9c,0x38b4,0xbb9cb8b4,0xb8b4bb9c,0x3bc738b4,0x361f3b21,0xbad2b4f2,0xb932bbe7,0x39a80000,0x39a83c00,0xb9a80000,0xb9a8bc00,0x3378b8b4,0x3b643b21,0xb82e34f2,0xba15bbe7,
0xb4f2bb9c,0x3c0038b4,0xb4f238b4,0xba79bb9c,0xba15bb9c,0x3b643102,0xad053a79,0xbad2bb21,0xbbe7b8b4,0x39a8b4f2,0x31023b9c,0xbb21ba79,0xbb640000,0x361fb9a8,0x361f3c00,0xbb64b9a8,
0xb8b438b4,0xbb9c,0x38b43b9c,0xbb9cb8b4,0xad053b9c,0xb61fbbe7,0x3a153a79,0xbbc7b744,0x37443b9c,0xb9a8ba79,0x3b2138b4,0xbbe7b4f2,0x3ad238b4,0xbb64b744,0x3bc734f2,0xbbfab102,
0x3c000000,0xbc000000,0x3c000000,0xbc000000,0x3ad2b8b4,0xbb643744,0x3bc7b4f2,0xbbfa3102,0x3744bb9c,0xb9a83a79,0x3b21b8b4,0xbbe734f2,0xad05bb9c,0xb61f3be7,0x3a15ba79,0xbbc73744,
0xb8b4b8b4,0x3b9c,0x38b4bb9c,0xbb9c38b4,0xbb640000,0x361f39a8,0x361fbc00,0xbb6439a8,0xbbe738b4,0x39a834f2,0x3102bb9c,0xbb213a79,0xba153b9c,0x3b64b102,0xad05ba79,0xbad23b21,
0xb4f23b9c,0x3c00b8b4,0xb4f2b8b4,0xba793b9c,0x337838b4,0x3b64bb21,0xb82eb4f2,0xba153be7,0x39a80000,0x39a8bc00,0xb9a80000,0xb9a83c00,0x3bc7b8b4,0x361fbb21,0xbad234f2,0xb9323be7,
0x3b9cbb9c,0xb8b4,0xbb9c38b4,0xb8b43b9c,0x3932bb9c,0xb61fb102,0xbbfa3a79,0xb82e3b21,0x3102b8b4,0xb9a834f2,0xbbe73b9c,0xb7443a79,0xb61f0000,0xbb6439a8,0xbb643c00,0xb61f39a8,
0xba7938b4,0xbc003b9c,0xba793b9c,0xb4f238b4,0xbbfa3b9c,0xbb643be7,0xb9323a79,0xb3783744,0xbb213b9c,0xb9a83a79,0xb74438b4,0xb10234f2,0xb82e38b4,0xb61f3744,0xb37834f2,0xad053102,
0x0,0x0,0x0,0x0,0x382eb8b4,0x361fb744,0x3378b4f2,0x2d05b102,0x3b21bb9c,0x39a8ba79,0x3744b8b4,0x3102b4f2,0x3bfabb9c,0x3b64bbe7,0x3932ba79,0x3378b744,
0x3a79b8b4,0x3c00bb9c,0x3a79bb9c,0x34f2b8b4,0x361f0000,0x3b64b9a8,0x3b64bc00,0x361fb9a8,0xb10238b4,0x39a8b4f2,0x3be7bb9c,0x3744ba79,0xb9323b9c,0x361f3102,0x3bfaba79,0x382ebb21,
0xbb9c3b9c,0x38b4,0x3b9cb8b4,0x38b4bb9c,0xbbc738b4,0xb61f3b21,0x3ad2b4f2,0x3932bbe7,0xb9a80000,0xb9a83c00,0x39a80000,0x39a8bc00,0xb378b8b4,0xbb643b21,0x382e34f2,0x3a15bbe7,
0x34f2bb9c,0xbc0038b4,0x34f238b4,0x3a79bb9c,0x3a15bb9c,0xbb643102,0x2d053a79,0x3ad2bb21,0x3be7b8b4,0xb9a8b4f2,0xb1023b9c,0x3b21ba79,0x3b640000,0xb61fb9a8,0xb61f3c00,0x3b64b9a8,
0x38b438b4,0xbb9c,0xb8b43b9c,0x3b9cb8b4,0x2d053b9c,0x361fbbe7,0xba153a79,0x3bc7b744,0xb7443b9c,0x39a8ba79,0xbb2138b4,0x3be7b4f2,0xbad238b4,0x3b64b744,0xbbc734f2,0x3bfab102,
0xbc000000,0x3c000000,0xbc000000,0x3c000000,0xbad2b8b4,0x3b643744,0xbbc7b4f2,0x3bfa3102,0xb744bb9c,0x39a83a79,0xbb21b8b4,0x3be734f2,0x2d05bb9c,0x361f3be7,0xba15ba79,0x3bc73744,
0x38b4b8b4,0x3b9c,0xb8b4bb9c,0x3b9c38b4,0x3b640000,0xb61f39a8,0xb61fbc00,0x3b6439a8,0x3be738b4,0xb9a834f2,0xb102bb9c,0x3b213a79,0x3a153b9c,0xbb64b102,0x2d05ba79,0x3ad23b21,
0x34f23b9c,0xbc00b8b4,0x34f2b8b4,0x3a793b9c,0xb37838b4,0xbb64bb21,0x382eb4f2,0x3a153be7,0xb9a80000,0xb9a8bc00,0x39a80000,0x39a83c00,0xbbc7b8b4,0xb61fbb21,0x3ad234f2,0x39323be7,
0xbb9cbb9c,0xb8b4,0x3b9c38b4,0x38b43b9c,0xb932bb9c,0x361fb102,0x3bfa3a79,0x382e3b21,0xb102b8b4,0x39a834f2,0x3be73b9c,0x37443a79,0x361f0000,0x3b6439a8,0x3b643c00,0x361f39a8,
0x3a7938b4,0x3c003b9c,0x3a793b9c,0x34f238b4,0x3bfa3b9c,0x3b643be7,0x39323a79,0x33783744,0x3b213b9c,0x39a83a79,0x374438b4,0x310234f2,0x382e38b4,0x361f3744,0x337834f2,0x2d053102,
0x3c00,0x3c00,0x3c00,0x3c00,0xbc000000,0xbc000000,0xbc000000,0xbc000000,0x3c00,0x2e463bf6,0x323e3bd9,0x34a53ba8,0xbc000000,0xbbf62e46,0xbbd9323e,0xbba834a5,
0x3c00,0x323e3bd9,0x361f3b64,0x38723aa7,0xbc000000,0xbbd9323e,0xbb64361f,0xbaa73872,0x3c00,0x34a53ba8,0x38723aa7,0x3a2f3913,0xbc000000,0xbba834a5,0xbaa73872,0xb9133a2f,
0x3c00,0x361f3b64,0x39a839a8,0x3b64361f,0xbc000000,0xbb64361f,0xb9a839a8,0xb61f3b64,0x3c00,0x378b3b0e,0x3aa73872,0x3bf62e46,0xbc000000,0xbb0e378b,0xb8723aa7,0xae463bf6,
0x3c00,0x38723aa7,0x3b64361f,0x3bd9b23e,0xbc000000,0xbaa73872,0xb61f3b64,0x323e3bd9,0x3c00,0x39133a2f,0x3bd9323e,0x3b0eb78b,0xbc000000,0xba2f3913,0xb23e3bd9,0x378b3b0e,
0x3c00,0x39a839a8,0x3c000000,0x39a8b9a8,0xbc000000,0xb9a839a8,0x80003c00,0x39a839a8,0x3c00,0x3a2f3913,0x3bd9b23e,0x378bbb0e,0xbc000000,0xb9133a2f,0x323e3bd9,0x3b0e378b,
0x3c00,0x3aa73872,0x3b64b61f,0x323ebbd9,0xbc000000,0xb8723aa7,0x361f3b64,0x3bd9323e,0x3c00,0x3b0e378b,0x3aa7b872,0xae46bbf6,0xbc000000,0xb78b3b0e,0x38723aa7,0x3bf6ae46,
0x3c00,0x3b64361f,0x39a8b9a8,0xb61fbb64,0xbc000000,0xb61f3b64,0x39a839a8,0x3b64b61f,0x3c00,0x3ba834a5,0x3872baa7,0xb913ba2f,0xbc000000,0xb4a53ba8,0x3aa73872,0x3a2fb913,
0x3c00,0x3bd9323e,0x361fbb64,0xbaa7b872,0xbc000000,0xb23e3bd9,0x3b64361f,0x3872baa7,0x3c00,0x3bf62e46,0x323ebbd9,0xbba8b4a5,0xbc000000,0xae463bf6,0x3bd9323e,0x34a5bba8,
0x3c00,0x3c00,0x3c00,0x3c00,0xbc000000,0xbc000000,0xbc000000,0xbc000000,0x361f3b64,0x378b3b0e,0x38723aa7,0x39133a2f,0xbb64361f,0xbb0e378b,0xbaa73872,0xba2f3913,
0x39a839a8,0x3aa73872,0x3b64361f,0x3bd9323e,0xb9a839a8,0xb8723aa7,0xb61f3b64,0xb23e3bd9,0x3b64361f,0x3bf62e46,0x3bd9b23e,0x3b0eb78b,0xb61f3b64,0xae463bf6,0x323e3bd9,0x378b3b0e,
0x3c000000,0x3b64b61f,0x39a8b9a8,0x361fbb64,0x80003c00,0x361f3b64,0x39a839a8,0x3b64361f,0x3b64b61f,0x3913ba2f,0x323ebbd9,0xb4a5bba8,0x361f3b64,0x3a2f3913,0x3bd9323e,0x3ba8b4a5,
0x39a8b9a8,0x323ebbd9,0xb61fbb64,0xbaa7b872,0x39a839a8,0x3bd9323e,0x3b64b61f,0x3872baa7,0x361fbb64,0xb4a5bba8,0xbaa7b872,0xbbf62e46,0x3b64361f,0x3ba8b4a5,0x3872baa7,0xae46bbf6,
0xbc00,0xb9a8b9a8,0xbc008000,0xb9a839a8,0x3c000000,0x39a8b9a8,0xbc00,0xb9a8b9a8,0xb61fbb64,0xbba8b4a5,0xbaa73872,0xae463bf6,0x3b64b61f,0x34a5bba8,0xb872baa7,0xbbf6ae46,
0xb9a8b9a8,0xbbd9323e,0xb61f3b64,0x38723aa7,0x39a8b9a8,0xb23ebbd9,0xbb64b61f,0xbaa73872,0xbb64b61f,0xba2f3913,0x323e3bd9,0x3ba834a5,0x361fbb64,0xb913ba2f,0xbbd9323e,0xb4a53ba8,
0xbc008000,0xb61f3b64,0x39a839a8,0x3b64b61f,0xbc00,0xbb64b61f,0xb9a839a8,0x361f3b64,0xbb64361f,0x2e463bf6,0x3bd9323e,0x378bbb0e,0xb61fbb64,0xbbf62e46,0xb23e3bd9,0x3b0e378b,
0xb9a839a8,0x38723aa7,0x3b64b61f,0xb23ebbd9,0xb9a8b9a8,0xbaa73872,0x361f3b64,0x3bd9b23e,0xb61f3b64,0x3b0e378b,0x3872baa7,0xba2fb913,0xbb64b61f,0xb78b3b0e,0x3aa73872,0x3913ba2f,
0x3c00,0x3c00,0x3c00,0x3c00,0xbc000000,0xbc000000,0xbc000000,0xbc000000,0x39a839a8,0x3a2f3913,0x3aa73872,0x3b0e378b,0xb9a839a8,0xb9133a2f,0xb8723aa7,0xb78b3b0e,
0x3c000000,0x3bd9b23e,0x3b64b61f,0x3aa7b872,0x80003c00,0x323e3bd9,0x361f3b64,0x38723aa7,0x39a8b9a8,0x378bbb0e,0x323ebbd9,0xae46bbf6,0x39a839a8,0x3b0e378b,0x3bd9323e,0x3bf6ae46,
0xbc00,0xb61fbb64,0xb9a8b9a8,0xbb64b61f,0x3c000000,0x3b64b61f,0x39a8b9a8,0x361fbb64,0xb9a8b9a8,0xbba8b4a5,0xbbd9323e,0xba2f3913,0x39a8b9a8,0x34a5bba8,0xb23ebbd9,0xb913ba2f,
0xbc008000,0xbaa73872,0xb61f3b64,0x323e3bd9,0xbc00,0xb872baa7,0xbb64b61f,0xbbd9323e,0xb9a839a8,0xae463bf6,0x38723aa7,0x3ba834a5,0xb9a8b9a8,0xbbf6ae46,0xbaa73872,0xb4a53ba8,
0x3c00,0x39a839a8,0x3c000000,0x39a8b9a8,0xbc000000,0xb9a839a8,0x80003c00,0x39a839a8,0x39a839a8,0x3bf6ae46,0x3872baa7,0xb4a5bba8,0xb9a839a8,0x2e463bf6,0x3aa73872,0x3ba8b4a5,
0x3c000000,0x3872baa7,0xb61fbb64,0xbbd9b23e,0x80003c00,0x3aa73872,0x3b64b61f,0x323ebbd9,0x39a8b9a8,0xb4a5bba8,0xbbd9b23e,0xb9133a2f,0x39a839a8,0x3ba8b4a5,0x323ebbd9,0xba2fb913,
0xbc00,0xbb64b61f,0xb9a839a8,0x361f3b64,0x3c000000,0x361fbb64,0xb9a8b9a8,0xbb64361f,0xb9a8b9a8,0xbb0e378b,0x323e3bd9,0x3bf62e46,0x39a8b9a8,0xb78bbb0e,0xbbd9323e,0xae463bf6,
0xbc008000,0xb23e3bd9,0x3b64361f,0x3872baa7,0xbc00,0xbbd9b23e,0xb61f3b64,0x3aa73872,0xb9a839a8,0x39133a2f,0x3aa7b872,0xb78bbb0e,0xb9a8b9a8,0xba2f3913,0x38723aa7,0x3b0eb78b,
0x3c00,0x3c00,0x3c00,0x3c00,0xbc000000,0xbc000000,0xbc000000,0xbc000000,0x3b64361f,0x3ba834a5,0x3bd9323e,0x3bf62e46,0xb61f3b64,0xb4a53ba8,0xb23e3bd9,0xae463bf6,
0x39a8b9a8,0x3872baa7,0x361fbb64,0x323ebbd9,0x39a839a8,0x3aa73872,0x3b64361f,0x3bd9323e,0xb61fbb64,0xb913ba2f,0xbaa7b872,0xbba8b4a5,0x3b64b61f,0x3a2fb913,0x3872baa7,0x34a5bba8,
0xbc008000,0xbb64361f,0xb9a839a8,0xb61f3b64,0xbc00,0xb61fbb64,0xb9a8b9a8,0xbb64b61f,0xb61f3b64,0x2e463bf6,0x38723aa7,0x3b0e378b,0xbb64b61f,0xbbf62e46,0xbaa73872,0xb78b3b0e,
0x39a839a8,0x3bd9323e,0x3b64b61f,0x3872baa7,0xb9a839a8,0xb23e3bd9,0x361f3b64,0x3aa73872,0x3b64b61f,0x378bbb0e,0xb23ebbd9,0xba2fb913,0x361f3b64,0x3b0e378b,0x3bd9b23e,0x3913ba2f,
0xbc00,0xb9a8b9a8,0xbc008000,0xb9a839a8,0x3c000000,0x39a8b9a8,0xbc00,0xb9a8b9a8,0xbb64b61f,0xbb0e378b,0xb23e3bd9,0x39133a2f,0x361fbb64,0xb78bbb0e,0xbbd9b23e,0xba2f3913,
0xb9a839a8,0x323e3bd9,0x3b64361f,0x3aa7b872,0xb9a8b9a8,0xbbd9323e,0xb61f3b64,0x38723aa7,0x361f3b64,0x3bf62e46,0x3872baa7,0xb78bbb0e,0xbb64361f,0xae463bf6,0x3aa73872,0x3b0eb78b,
0x3c000000,0x361fbb64,0xb9a8b9a8,0xbb64361f,0x80003c00,0x3b64361f,0x39a8b9a8,0xb61fbb64,0x361fbb64,0xba2fb913,0xbaa73872,0x34a53ba8,0x3b64361f,0x3913ba2f,0xb872baa7,0xbba834a5,
0xb9a8b9a8,0xbaa73872,0x361f3b64,0x3bd9b23e,0x39a8b9a8,0xb872baa7,0xbb64361f,0x323e3bd9,0xbb64361f,0x34a53ba8,0x3bd9b23e,0xae46bbf6,0xb61fbb64,0xbba834a5,0x323e3bd9,0x3bf6ae46,
0x3c00,0x3c00,0x3c00,0x3c00,0xbc000000,0xbc000000,0xbc000000,0xbc000000,0x3c000000,0x3bf6ae46,0x3bd9b23e,0x3ba8b4a5,0x80003c00,0x2e463bf6,0x323e3bd9,0x34a53ba8,
0xbc00,0xb23ebbd9,0xb61fbb64,0xb872baa7,0x3c000000,0x3bd9b23e,0x3b64b61f,0x3aa7b872,0xbc008000,0xbba834a5,0xbaa73872,0xb9133a2f,0xbc00,0xb4a5bba8,0xb872baa7,0xba2fb913,
0x3c00,0x361f3b64,0x39a839a8,0x3b64361f,0xbc000000,0xbb64361f,0xb9a839a8,0xb61f3b64,0x3c000000,0x3b0eb78b,0x3872baa7,0x2e46bbf6,0x80003c00,0x378b3b0e,0x3aa73872,0x3bf62e46,
0xbc00,0xb872baa7,0xbb64b61f,0xbbd9323e,0x3c000000,0x3aa7b872,0x361fbb64,0xb23ebbd9,0xbc008000,0xba2f3913,0xb23e3bd9,0x378b3b0e,0xbc00,0xb913ba2f,0xbbd9b23e,0xbb0e378b,
0x3c00,0x39a839a8,0x3c000000,0x39a8b9a8,0xbc000000,0xb9a839a8,0x80003c00,0x39a839a8,0x3c000000,0x3913ba2f,0xb23ebbd9,0xbb0eb78b,0x80003c00,0x3a2f3913,0x3bd9b23e,0x378bbb0e,
0xbc00,0xbaa7b872,0xbb64361f,0xb23e3bd9,0x3c000000,0x3872baa7,0xb61fbb64,0xbbd9b23e,0xbc008000,0xb78b3b0e,0x38723aa7,0x3bf6ae46,0xbc00,0xbb0eb78b,0xbaa73872,0x2e463bf6,
0x3c00,0x3b64361f,0x39a8b9a8,0xb61fbb64,0xbc000000,0xb61f3b64,0x39a839a8,0x3b64b61f,0x3c000000,0x34a5bba8,0xbaa7b872,0xba2f3913,0x80003c00,0x3ba834a5,0x3872baa7,0xb913ba2f,
0xbc00,0xbbd9b23e,0xb61f3b64,0x3aa73872,0x3c000000,0x323ebbd9,0xbb64b61f,0xb8723aa7,0xbc008000,0xae463bf6,0x3bd9323e,0x34a5bba8,0xbc00,0xbbf6ae46,0xb23e3bd9,0x3ba834a5,
0x3c00,0x3c00,0x3c00,0x3c00,0xbc000000,0xbc000000,0xbc000000,0xbc000000,0x3b64b61f,0x3b0eb78b,0x3aa7b872,0x3a2fb913,0x361f3b64,0x378b3b0e,0x38723aa7,0x39133a2f,
0xb9a8b9a8,0xbaa7b872,0xbb64b61f,0xbbd9b23e,0x39a8b9a8,0x3872baa7,0x361fbb64,0x323ebbd9,0xb61f3b64,0xae463bf6,0x323e3bd9,0x378b3b0e,0xbb64b61f,0xbbf6ae46,0xbbd9323e,0xbb0e378b,
0x3c000000,0x3b64b61f,0x39a8b9a8,0x361fbb64,0x80003c00,0x361f3b64,0x39a839a8,0x3b64361f,0xb61fbb64,0xba2fb913,0xbbd9b23e,0xbba834a5,0x3b64b61f,0x3913ba2f,0x323ebbd9,0xb4a5bba8,
0xb9a839a8,0xb23e3bd9,0x361f3b64,0x3aa73872,0xb9a8b9a8,0xbbd9b23e,0xbb64361f,0xb8723aa7,0x3b64361f,0x3ba8b4a5,0x3872baa7,0xae46bbf6,0xb61f3b64,0x34a53ba8,0x3aa73872,0x3bf6ae46,
0xbc00,0xb9a8b9a8,0xbc008000,0xb9a839a8,0x3c000000,0x39a8b9a8,0xbc00,0xb9a8b9a8,0xbb64361f,0xb4a53ba8,0x38723aa7,0x3bf62e46,0xb61fbb64,0xbba8b4a5,0xbaa73872,0xae463bf6,
0x39a839a8,0x3bd9b23e,0x361fbb64,0xb872baa7,0xb9a839a8,0x323e3bd9,0x3b64361f,0x3aa7b872,0x361fbb64,0xb913ba2f,0xbbd9323e,0xb4a53ba8,0x3b64361f,0x3a2fb913,0xb23ebbd9,0xbba8b4a5,
0xbc008000,0xb61f3b64,0x39a839a8,0x3b64b61f,0xbc00,0xbb64b61f,0xb9a839a8,0x361f3b64,0x361f3b64,0x3bf6ae46,0x323ebbd9,0xbb0eb78b,0xbb64361f,0x2e463bf6,0x3bd9323e,0x378bbb0e,
0x39a8b9a8,0xb872baa7,0xbb64361f,0x323e3bd9,0x39a839a8,0x3aa7b872,0xb61fbb64,0xbbd9323e,0xbb64b61f,0xb78b3b0e,0x3aa73872,0x3913ba2f,0x361fbb64,0xbb0eb78b,0xb8723aa7,0x3a2f3913,
0x3c00,0x3c00,0x3c00,0x3c00,0xbc000000,0xbc000000,0xbc000000,0xbc000000,0x39a8b9a8,0x3913ba2f,0x3872baa7,0x378bbb0e,0x39a839a8,0x3a2f3913,0x3aa73872,0x3b0e378b,
0xbc008000,0xbbd9323e,0xbb64361f,0xbaa73872,0xbc00,0xb23ebbd9,0xb61fbb64,0xb872baa7,0x39a839a8,0x3b0e378b,0x3bd9323e,0x3bf6ae46,0xb9a839a8,0xb78b3b0e,0xb23e3bd9,0x2e463bf6,
0xbc00,0xb61fbb64,0xb9a8b9a8,0xbb64b61f,0x3c000000,0x3b64b61f,0x39a8b9a8,0x361fbb64,0xb9a839a8,0xb4a53ba8,0x323e3bd9,0x39133a2f,0xb9a8b9a8,0xbba8b4a5,0xbbd9323e,0xba2f3913,
0x3c000000,0x3aa7b872,0x361fbb64,0xb23ebbd9,0x80003c00,0x38723aa7,0x3b64361f,0x3bd9b23e,0xb9a8b9a8,0xbbf6ae46,0xbaa73872,0xb4a53ba8,0x39a8b9a8,0x2e46bbf6,0xb872baa7,0xbba8b4a5,
0x3c00,0x39a839a8,0x3c000000,0x39a8b9a8,0xbc000000,0xb9a839a8,0x80003c00,0x39a839a8,0x39a8b9a8,0xae46bbf6,0xbaa7b872,0xbba834a5,0x39a839a8,0x3bf6ae46,0x3872baa7,0xb4a5bba8,
0xbc008000,0xb8723aa7,0x361f3b64,0x3bd9323e,0xbc00,0xbaa7b872,0xbb64361f,0xb23e3bd9,0x39a839a8,0x3ba8b4a5,0x323ebbd9,0xba2fb913,0xb9a839a8,0x34a53ba8,0x3bd9323e,0x3913ba2f,
0xbc00,0xbb64b61f,0xb9a839a8,0x361f3b64,0x3c000000,0x361fbb64,0xb9a8b9a8,0xbb64361f,0xb9a839a8,0x378b3b0e,0x3bd9b23e,0x2e46bbf6,0xb9a8b9a8,0xbb0e378b,0x323e3bd9,0x3bf62e46,
0x3c000000,0x323ebbd9,0xbb64b61f,0xb8723aa7,0x80003c00,0x3bd9323e,0x361fbb64,0xbaa7b872,0xb9a8b9a8,0xba2f3913,0x38723aa7,0x3b0eb78b,0x39a8b9a8,0xb913ba2f,0xbaa73872,0x378b3b0e,
0x3c00,0x3c00,0x3c00,0x3c00,0xbc000000,0xbc000000,0xbc000000,0xbc000000,0x361fbb64,0x34a5bba8,0x323ebbd9,0x2e46bbf6,0x3b64361f,0x3ba834a5,0x3bd9323e,0x3bf62e46,
0xb9a839a8,0xb8723aa7,0xb61f3b64,0xb23e3bd9,0xb9a8b9a8,0xbaa7b872,0xbb64b61f,0xbbd9b23e,0x3b64b61f,0x3a2fb913,0x3872baa7,0x34a5bba8,0x361f3b64,0x39133a2f,0x3aa73872,0x3ba834a5,
0xbc008000,0xbb64361f,0xb9a839a8,0xb61f3b64,0xbc00,0xb61fbb64,0xb9a8b9a8,0xbb64b61f,0x3b64361f,0x3bf6ae46,0x3aa7b872,0x378bbb0e,0xb61f3b64,0x2e463bf6,0x38723aa7,0x3b0e378b,
0xb9a8b9a8,0xbbd9b23e,0xbb64361f,0xb8723aa7,0x39a8b9a8,0x323ebbd9,0xb61fbb64,0xbaa7b872,0x361f3b64,0x3b0e378b,0x3bd9b23e,0x3913ba2f,0xbb64361f,0xb78b3b0e,0x323e3bd9,0x3a2f3913,
0xbc00,0xb9a8b9a8,0xbc008000,0xb9a839a8,0x3c000000,0x39a8b9a8,0xbc00,0xb9a8b9a8,0xb61f3b64,0x378b3b0e,0x3bd9323e,0x3a2fb913,0xbb64b61f,0xbb0e378b,0xb23e3bd9,0x39133a2f,
0x39a8b9a8,0xb23ebbd9,0xbb64b61f,0xbaa73872,0x39a839a8,0x3bd9b23e,0x361fbb64,0xb872baa7,0xbb64361f,0xae463bf6,0x3aa73872,0x3b0eb78b,0xb61fbb64,0xbbf6ae46,0xb8723aa7,0x378b3b0e,
0x3c000000,0x361fbb64,0xb9a8b9a8,0xbb64361f,0x80003c00,0x3b64361f,0x39a8b9a8,0xb61fbb64,0xbb64b61f,0xb9133a2f,0x38723aa7,0x3ba8b4a5,0x361fbb64,0xba2fb913,0xbaa73872,0x34a53ba8,
0x39a839a8,0x3aa7b872,0xb61fbb64,0xbbd9323e,0xb9a839a8,0x38723aa7,0x3b64b61f,0xb23ebbd9,0xb61fbb64,0xbba834a5,0x323e3bd9,0x3bf6ae46,0x3b64b61f,0xb4a5bba8,0xbbd9323e,0x2e463bf6,
0x80003c00,0x80003c00,0x80003c00,0x80003c00,0x3c000000,0x3c000000,0x3c000000,0x3c000000,0x8000bc00,0x2e46bbf6,0x323ebbd9,0x34a5bba8,0xbc000000,0xbbf6ae46,0xbbd9b23e,0xbba8b4a5,
0x80003c00,0xb23e3bd9,0xb61f3b64,0xb8723aa7,0x3c000000,0x3bd9323e,0x3b64361f,0x3aa73872,0x8000bc00,0x34a5bba8,0x3872baa7,0x3a2fb913,0xbc000000,0xbba8b4a5,0xbaa7b872,0xb913ba2f,
0x80003c00,0xb61f3b64,0xb9a839a8,0xbb64361f,0x3c000000,0x3b64361f,0x39a839a8,0x361f3b64,0x8000bc00,0x378bbb0e,0x3aa7b872,0x3bf6ae46,0xbc000000,0xbb0eb78b,0xb872baa7,0xae46bbf6,
0x80003c00,0xb8723aa7,0xbb64361f,0xbbd9b23e,0x3c000000,0x3aa73872,0x361f3b64,0xb23e3bd9,0x8000bc00,0x3913ba2f,0x3bd9b23e,0x3b0e378b,0xbc000000,0xba2fb913,0xb23ebbd9,0x378bbb0e,
0x80003c00,0xb9a839a8,0xbc000000,0xb9a8b9a8,0x3c000000,0x39a839a8,0x3c00,0xb9a839a8,0x8000bc00,0x3a2fb913,0x3bd9323e,0x378b3b0e,0xbc000000,0xb913ba2f,0x323ebbd9,0x3b0eb78b,
0x80003c00,0xbaa73872,0xbb64b61f,0xb23ebbd9,0x3c000000,0x38723aa7,0xb61f3b64,0xbbd9323e,0x8000bc00,0x3b0eb78b,0x3aa73872,0xae463bf6,0xbc000000,0xb78bbb0e,0x3872baa7,0x3bf62e46,
0x80003c00,0xbb64361f,0xb9a8b9a8,0x361fbb64,0x3c000000,0x361f3b64,0xb9a839a8,0xbb64b61f,0x8000bc00,0x3ba8b4a5,0x38723aa7,0xb9133a2f,0xbc000000,0xb4a5bba8,0x3aa7b872,0x3a2f3913,
0x80003c00,0xbbd9323e,0xb61fbb64,0x3aa7b872,0x3c000000,0x323e3bd9,0xbb64361f,0xb872baa7,0x8000bc00,0x3bf6ae46,0x323e3bd9,0xbba834a5,0xbc000000,0xae46bbf6,0x3bd9b23e,0x34a53ba8,
0x80003c00,0x80003c00,0x80003c00,0x80003c00,0x3c000000,0x3c000000,0x3c000000,0x3c000000,0x361fbb64,0x378bbb0e,0x3872baa7,0x3913ba2f,0xbb64b61f,0xbb0eb78b,0xbaa7b872,0xba2fb913,
0xb9a839a8,0xbaa73872,0xbb64361f,0xbbd9323e,0x39a839a8,0x38723aa7,0x361f3b64,0x323e3bd9,0x3b64b61f,0x3bf6ae46,0x3bd9323e,0x3b0e378b,0xb61fbb64,0xae46bbf6,0x323ebbd9,0x378bbb0e,
0xbc000000,0xbb64b61f,0xb9a8b9a8,0xb61fbb64,0x3c00,0xb61f3b64,0xb9a839a8,0xbb64361f,0x3b64361f,0x39133a2f,0x323e3bd9,0xb4a53ba8,0x361fbb64,0x3a2fb913,0x3bd9b23e,0x3ba834a5,
0xb9a8b9a8,0xb23ebbd9,0x361fbb64,0x3aa7b872,0xb9a839a8,0xbbd9323e,0xbb64b61f,0xb872baa7,0x361f3b64,0xb4a53ba8,0xbaa73872,0xbbf6ae46,0x3b64b61f,0x3ba834a5,0x38723aa7,0xae463bf6,
0x8000bc00,0x39a8b9a8,0x3c008000,0x39a839a8,0xbc000000,0xb9a8b9a8,0x8000bc00,0x39a8b9a8,0xb61f3b64,0xbba834a5,0xbaa7b872,0xae46bbf6,0x3b64361f,0x34a53ba8,0xb8723aa7,0xbbf62e46,
0x39a8b9a8,0x3bd9323e,0x361f3b64,0xb8723aa7,0xb9a8b9a8,0x323ebbd9,0x3b64b61f,0x3aa73872,0xbb64361f,0xba2fb913,0x323ebbd9,0x3ba8b4a5,0x361f3b64,0xb9133a2f,0xbbd9b23e,0xb4a5bba8,
0x3c008000,0x361f3b64,0xb9a839a8,0xbb64b61f,0x8000bc00,0x3b64b61f,0x39a839a8,0xb61f3b64,0xbb64b61f,0x2e46bbf6,0x3bd9b23e,0x378b3b0e,0xb61f3b64,0xbbf6ae46,0xb23ebbd9,0x3b0eb78b,
0x39a839a8,0xb8723aa7,0xbb64b61f,0x323ebbd9,0x39a8b9a8,0x3aa73872,0xb61f3b64,0xbbd9b23e,0xb61fbb64,0x3b0eb78b,0x38723aa7,0xba2f3913,0xbb64361f,0xb78bbb0e,0x3aa7b872,0x39133a2f,
0x80003c00,0x80003c00,0x80003c00,0x80003c00,0x3c000000,0x3c000000,0x3c000000,0x3c000000,0x39a8b9a8,0x3a2fb913,0x3aa7b872,0x3b0eb78b,0xb9a8b9a8,0xb913ba2f,0xb872baa7,0xb78bbb0e,
0xbc000000,0xbbd9b23e,0xbb64b61f,0xbaa7b872,0x3c00,0xb23e3bd9,0xb61f3b64,0xb8723aa7,0x39a839a8,0x378b3b0e,0x323e3bd9,0xae463bf6,0x39a8b9a8,0x3b0eb78b,0x3bd9b23e,0x3bf62e46,
0x8000bc00,0x361fbb64,0x39a8b9a8,0x3b64b61f,0xbc000000,0xbb64b61f,0xb9a8b9a8,0xb61fbb64,0xb9a839a8,0xbba834a5,0xbbd9b23e,0xba2fb913,0x39a839a8,0x34a53ba8,0xb23e3bd9,0xb9133a2f,
0x3c008000,0x3aa73872,0x361f3b64,0xb23e3bd9,0x8000bc00,0x3872baa7,0x3b64b61f,0x3bd9323e,0xb9a8b9a8,0xae46bbf6,0x3872baa7,0x3ba8b4a5,0xb9a839a8,0xbbf62e46,0xbaa7b872,0xb4a5bba8,
0x80003c00,0xb9a839a8,0xbc000000,0xb9a8b9a8,0x3c000000,0x39a839a8,0x3c00,0xb9a839a8,0x39a8b9a8,0x3bf62e46,0x38723aa7,0xb4a53ba8,0xb9a8b9a8,0x2e46bbf6,0x3aa7b872,0x3ba834a5,
0xbc000000,0xb872baa7,0x361fbb64,0x3bd9b23e,0x3c00,0xbaa73872,0xbb64b61f,0xb23ebbd9,0x39a839a8,0xb4a53ba8,0xbbd9323e,0xb913ba2f,0x39a8b9a8,0x3ba834a5,0x323e3bd9,0xba2f3913,
0x8000bc00,0x3b64b61f,0x39a839a8,0xb61f3b64,0xbc000000,0xb61fbb64,0x39a8b9a8,0x3b64361f,0xb9a839a8,0xbb0eb78b,0x323ebbd9,0x3bf6ae46,0x39a839a8,0xb78b3b0e,0xbbd9b23e,0xae46bbf6,
0x3c008000,0x323e3bd9,0xbb64361f,0xb872baa7,0x8000bc00,0x3bd9b23e,0x361f3b64,0xbaa73872,0xb9a8b9a8,0x3913ba2f,0x3aa73872,0xb78b3b0e,0xb9a839a8,0xba2fb913,0x3872baa7,0x3b0e378b,
0x80003c00,0x80003c00,0x80003c00,0x80003c00,0x3c000000,0x3c000000,0x3c000000,0x3c000000,0x3b64b61f,0x3ba8b4a5,0x3bd9b23e,0x3bf6ae46,0xb61fbb64,0xb4a5bba8,0xb23ebbd9,0xae46bbf6,
0xb9a8b9a8,0xb872baa7,0xb61fbb64,0xb23ebbd9,0xb9a839a8,0xbaa73872,0xbb64361f,0xbbd9323e,0xb61f3b64,0xb9133a2f,0xbaa73872,0xbba834a5,0x3b64361f,0x3a2f3913,0x38723aa7,0x34a53ba8,
0x3c008000,0x3b64361f,0x39a839a8,0x361f3b64,0x8000bc00,0x361fbb64,0x39a8b9a8,0x3b64b61f,0xb61fbb64,0x2e46bbf6,0x3872baa7,0x3b0eb78b,0xbb64361f,0xbbf6ae46,0xbaa7b872,0xb78bbb0e,
0xb9a839a8,0xbbd9323e,0xbb64b61f,0xb872baa7,0x39a839a8,0x323e3bd9,0xb61f3b64,0xbaa73872,0x3b64361f,0x378b3b0e,0xb23e3bd9,0xba2f3913,0x361fbb64,0x3b0eb78b,0x3bd9323e,0x39133a2f,
0x8000bc00,0x39a8b9a8,0x3c008000,0x39a839a8,0xbc000000,0xb9a8b9a8,0x8000bc00,0x39a8b9a8,0xbb64361f,0xbb0eb78b,0xb23ebbd9,0x3913ba2f,0x361f3b64,0xb78b3b0e,0xbbd9323e,0xba2fb913,
0x39a839a8,0xb23e3bd9,0xbb64361f,0xbaa7b872,0x39a8b9a8,0x3bd9323e,0x361f3b64,0xb8723aa7,0x361fbb64,0x3bf6ae46,0x38723aa7,0xb78b3b0e,0xbb64b61f,0xae46bbf6,0x3aa7b872,0x3b0e378b,
0xbc000000,0xb61fbb64,0x39a8b9a8,0x3b64361f,0x3c00,0xbb64361f,0xb9a8b9a8,0x361fbb64,0x361f3b64,0xba2f3913,0xbaa7b872,0x34a5bba8,0x3b64b61f,0x39133a2f,0xb8723aa7,0xbba8b4a5,
0x39a8b9a8,0x3aa73872,0xb61f3b64,0xbbd9b23e,0xb9a8b9a8,0x3872baa7,0x3b64361f,0xb23e3bd9,0xbb64b61f,0x34a5bba8,0x3bd9323e,0xae463bf6,0xb61f3b64,0xbba8b4a5,0x323ebbd9,0x3bf62e46,
0x80003c00,0x80003c00,0x80003c00,0x80003c00,0x3c000000,0x3c000000,0x3c000000,0x3c000000,0x3c008000,0x3bf62e46,0x3bd9323e,0x3ba834a5,0x8000bc00,0x2e46bbf6,0x323ebbd9,0x34a5bba8,
0x8000bc00,0x323ebbd9,0x361fbb64,0x3872baa7,0xbc000000,0xbbd9b23e,0xbb64b61f,0xbaa7b872,0xbc000000,0xbba8b4a5,0xbaa7b872,0xb913ba2f,0x3c00,0xb4a53ba8,0xb8723aa7,0xba2f3913,
0x80003c00,0xb61f3b64,0xb9a839a8,0xbb64361f,0x3c000000,0x3b64361f,0x39a839a8,0x361f3b64,0x3c008000,0x3b0e378b,0x38723aa7,0x2e463bf6,0x8000bc00,0x378bbb0e,0x3aa7b872,0x3bf6ae46,
0x8000bc00,0x3872baa7,0x3b64b61f,0x3bd9323e,0xbc000000,0xbaa7b872,0xb61fbb64,0x323ebbd9,0xbc000000,0xba2fb913,0xb23ebbd9,0x378bbb0e,0x3c00,0xb9133a2f,0xbbd9323e,0xbb0eb78b,
0x80003c00,0xb9a839a8,0xbc000000,0xb9a8b9a8,0x3c000000,0x39a839a8,0x3c00,0xb9a839a8,0x3c008000,0x39133a2f,0xb23e3bd9,0xbb0e378b,0x8000bc00,0x3a2fb913,0x3bd9323e,0x378b3b0e,
0x8000bc00,0x3aa7b872,0x3b64361f,0x323e3bd9,0xbc000000,0xb872baa7,0x361fbb64,0x3bd9b23e,0xbc000000,0xb78bbb0e,0x3872baa7,0x3bf62e46,0x3c00,0xbb0e378b,0xbaa7b872,0x2e46bbf6,
0x80003c00,0xbb64361f,0xb9a8b9a8,0x361fbb64,0x3c000000,0x361f3b64,0xb9a839a8,0xbb64b61f,0x3c008000,0x34a53ba8,0xbaa73872,0xba2fb913,0x8000bc00,0x3ba8b4a5,0x38723aa7,0xb9133a2f,
0x8000bc00,0x3bd9b23e,0x361f3b64,0xbaa73872,0xbc000000,0xb23ebbd9,0x3b64b61f,0x38723aa7,0xbc000000,0xae46bbf6,0x3bd9b23e,0x34a53ba8,0x3c00,0xbbf62e46,0xb23ebbd9,0x3ba8b4a5,
0x80003c00,0x80003c00,0x80003c00,0x80003c00,0x3c000000,0x3c000000,0x3c000000,0x3c000000,0x3b64361f,0x3b0e378b,0x3aa73872,0x3a2f3913,0x361fbb64,0x378bbb0e,0x3872baa7,0x3913ba2f,
0x39a8b9a8,0x3aa7b872,0x3b64b61f,0x3bd9b23e,0xb9a8b9a8,0xb872baa7,0xb61fbb64,0xb23ebbd9,0xb61fbb64,0xae46bbf6,0x323ebbd9,0x378bbb0e,0xbb64361f,0xbbf62e46,0xbbd9b23e,0xbb0eb78b,
0xbc000000,0xbb64b61f,0xb9a8b9a8,0xb61fbb64,0x3c00,0xb61f3b64,0xb9a839a8,0xbb64361f,0xb61f3b64,0xba2f3913,0xbbd9323e,0xbba8b4a5,0x3b64361f,0x39133a2f,0x323e3bd9,0xb4a53ba8,
0x39a839a8,0x323e3bd9,0xb61f3b64,0xbaa73872,0x39a8b9a8,0x3bd9b23e,0x3b64361f,0x38723aa7,0x3b64b61f,0x3ba834a5,0x38723aa7,0xae463bf6,0xb61fbb64,0x34a5bba8,0x3aa7b872,0x3bf62e46,
0x8000bc00,0x39a8b9a8,0x3c008000,0x39a839a8,0xbc000000,0xb9a8b9a8,0x8000bc00,0x39a8b9a8,0xbb64b61f,0xb4a5bba8,0x3872baa7,0x3bf6ae46,0xb61f3b64,0xbba834a5,0xbaa7b872,0xae46bbf6,
0xb9a839a8,0xbbd9b23e,0xb61fbb64,0x3872baa7,0x39a839a8,0xb23e3bd9,0xbb64361f,0xbaa7b872,0x361f3b64,0xb9133a2f,0xbbd9b23e,0xb4a5bba8,0x3b64b61f,0x3a2f3913,0xb23e3bd9,0xbba834a5,
0x3c008000,0x361f3b64,0xb9a839a8,0xbb64b61f,0x8000bc00,0x3b64b61f,0x39a839a8,0xb61f3b64,0x361fbb64,0x3bf62e46,0x323e3bd9,0xbb0e378b,0xbb64b61f,0x2e46bbf6,0x3bd9b23e,0x378b3b0e,
0xb9a8b9a8,0x3872baa7,0x3b64361f,0xb23e3bd9,0xb9a839a8,0xbaa7b872,0x361fbb64,0x3bd9323e,0xbb64361f,0xb78bbb0e,0x3aa7b872,0x39133a2f,0x361f3b64,0xbb0e378b,0xb872baa7,0x3a2fb913,
0x80003c00,0x80003c00,0x80003c00,0x80003c00,0x3c000000,0x3c000000,0x3c000000,0x3c000000,0x39a839a8,0x39133a2f,0x38723aa7,0x378b3b0e,0x39a8b9a8,0x3a2fb913,0x3aa7b872,0x3b0eb78b,
0x3c008000,0x3bd9323e,0x3b64361f,0x3aa73872,0x8000bc00,0x323ebbd9,0x361fbb64,0x3872baa7,0x39a8b9a8,0x3b0eb78b,0x3bd9b23e,0x3bf62e46,0xb9a8b9a8,0xb78bbb0e,0xb23ebbd9,0x2e46bbf6,
0x8000bc00,0x361fbb64,0x39a8b9a8,0x3b64b61f,0xbc000000,0xbb64b61f,0xb9a8b9a8,0xb61fbb64,0xb9a8b9a8,0xb4a5bba8,0x323ebbd9,0x3913ba2f,0xb9a839a8,0xbba834a5,0xbbd9b23e,0xba2fb913,
0xbc000000,0xbaa7b872,0xb61fbb64,0x323ebbd9,0x3c00,0xb8723aa7,0xbb64361f,0xbbd9b23e,0xb9a839a8,0xbbf62e46,0xbaa7b872,0xb4a5bba8,0x39a839a8,0x2e463bf6,0xb8723aa7,0xbba834a5,
0x80003c00,0xb9a839a8,0xbc000000,0xb9a8b9a8,0x3c000000,0x39a839a8,0x3c00,0xb9a839a8,0x39a839a8,0xae463bf6,0xbaa73872,0xbba8b4a5,0x39a8b9a8,0x3bf62e46,0x38723aa7,0xb4a53ba8,
0x3c008000,0x38723aa7,0xb61f3b64,0xbbd9323e,0x8000bc00,0x3aa7b872,0x3b64361f,0x323e3bd9,0x39a8b9a8,0x3ba834a5,0x323e3bd9,0xba2f3913,0xb9a8b9a8,0x34a5bba8,0x3bd9b23e,0x39133a2f,
0x8000bc00,0x3b64b61f,0x39a839a8,0xb61f3b64,0xbc000000,0xb61fbb64,0x39a8b9a8,0x3b64361f,0xb9a8b9a8,0x378bbb0e,0x3bd9323e,0x2e463bf6,0xb9a839a8,0xbb0eb78b,0x323ebbd9,0x3bf6ae46,
0xbc000000,0xb23ebbd9,0x3b64b61f,0x38723aa7,0x3c00,0xbbd9323e,0xb61fbb64,0x3aa7b872,0xb9a839a8,0xba2fb913,0x3872baa7,0x3b0e378b,0x39a839a8,0xb9133a2f,0xbaa7b872,0x378bbb0e,
0x80003c00,0x80003c00,0x80003c00,0x80003c00,0x3c000000,0x3c000000,0x3c000000,0x3c000000,0x361f3b64,0x34a53ba8,0x323e3bd9,0x2e463bf6,0x3b64b61f,0x3ba8b4a5,0x3bd9b23e,0x3bf6ae46,
0x39a839a8,0x38723aa7,0x361f3b64,0x323e3bd9,0x39a8b9a8,0x3aa7b872,0x3b64b61f,0x3bd9b23e,0x3b64361f,0x3a2f3913,0x38723aa7,0x34a53ba8,0x361fbb64,0x3913ba2f,0x3aa7b872,0x3ba8b4a5,
0x3c008000,0x3b64361f,0x39a839a8,0x361f3b64,0x8000bc00,0x361fbb64,0x39a8b9a8,0x3b64b61f,0x3b64b61f,0x3bf62e46,0x3aa73872,0x378b3b0e,0xb61fbb64,0x2e46bbf6,0x3872baa7,0x3b0eb78b,
0x39a8b9a8,0x3bd9b23e,0x3b64361f,0x38723aa7,0xb9a8b9a8,0xb23ebbd9,0x361fbb64,0x3aa7b872,0x361fbb64,0x3b0eb78b,0x3bd9323e,0x39133a2f,0xbb64b61f,0xb78bbb0e,0x323ebbd9,0x3a2fb913,
0x8000bc00,0x39a8b9a8,0x3c008000,0x39a839a8,0xbc000000,0xb9a8b9a8,0x8000bc00,0x39a8b9a8,0xb61fbb64,0x378bbb0e,0x3bd9b23e,0x3a2f3913,0xbb64361f,0xbb0eb78b,0xb23ebbd9,0x3913ba2f,
0xb9a8b9a8,0x323ebbd9,0x3b64b61f,0x3aa73872,0xb9a839a8,0xbbd9b23e,0xb61fbb64,0x3872baa7,0xbb64b61f,0xae46bbf6,0x3aa7b872,0x3b0e378b,0xb61f3b64,0xbbf62e46,0xb872baa7,0x378bbb0e,
0xbc000000,0xb61fbb64,0x39a8b9a8,0x3b64361f,0x3c00,0xbb64361f,0xb9a8b9a8,0x361fbb64,0xbb64361f,0xb913ba2f,0x3872baa7,0x3ba834a5,0x361f3b64,0xba2f3913,0xbaa7b872,0x34a5bba8,
0xb9a839a8,0xbaa7b872,0x361fbb64,0x3bd9323e,0x39a839a8,0xb8723aa7,0xbb64b61f,0x323ebbd9,0xb61f3b64,0xbba8b4a5,0x323ebbd9,0x3bf62e46,0x3b64361f,0xb4a53ba8,0xbbd9b23e,0x2e46bbf6,
0x3c00,0x3c000000,0xbc00,0xbc008000,0xbc000000,0x80003c00,0x3c000000,0xbc00,0x3c00,0x3bf6ae46,0xb23ebbd9,0xbba834a5,0xbc000000,0x2e463bf6,0x3bd9b23e,0xb4a5bba8,
0x3c00,0x3bd9b23e,0xb61fbb64,0xbaa73872,0xbc000000,0x323e3bd9,0x3b64b61f,0xb872baa7,0x3c00,0x3ba8b4a5,0xb872baa7,0xb9133a2f,0xbc000000,0x34a53ba8,0x3aa7b872,0xba2fb913,
0x3c00,0x3b64b61f,0xb9a8b9a8,0xb61f3b64,0xbc000000,0x361f3b64,0x39a8b9a8,0xbb64b61f,0x3c00,0x3b0eb78b,0xbaa7b872,0xae463bf6,0xbc000000,0x378b3b0e,0x3872baa7,0xbbf6ae46,
0x3c00,0x3aa7b872,0xbb64b61f,0x323e3bd9,0xbc000000,0x38723aa7,0x361fbb64,0xbbd9323e,0x3c00,0x3a2fb913,0xbbd9b23e,0x378b3b0e,0xbc000000,0x39133a2f,0x323ebbd9,0xbb0e378b,
0x3c00,0x39a8b9a8,0xbc008000,0x39a839a8,0xbc000000,0x39a839a8,0xbc00,0xb9a839a8,0x3c00,0x3913ba2f,0xbbd9323e,0x3b0e378b,0xbc000000,0x3a2f3913,0xb23ebbd9,0xb78b3b0e,
0x3c00,0x3872baa7,0xbb64361f,0x3bd9323e,0xbc000000,0x3aa73872,0xb61fbb64,0xb23e3bd9,0x3c00,0x378bbb0e,0xbaa73872,0x3bf6ae46,0xbc000000,0x3b0e378b,0xb872baa7,0x2e463bf6,
0x3c00,0x361fbb64,0xb9a839a8,0x3b64b61f,0xbc000000,0x3b64361f,0xb9a8b9a8,0x361f3b64,0x3c00,0x34a5bba8,0xb8723aa7,0x3a2fb913,0xbc000000,0x3ba834a5,0xbaa7b872,0x39133a2f,
0x3c00,0x323ebbd9,0xb61f3b64,0x3872baa7,0xbc000000,0x3bd9323e,0xbb64b61f,0x3aa73872,0x3c00,0x2e46bbf6,0xb23e3bd9,0x34a5bba8,0xbc000000,0x3bf62e46,0xbbd9b23e,0x3ba834a5,
0x3c00,0x3c000000,0xbc00,0xbc008000,0xbc000000,0x80003c00,0x3c000000,0xbc00,0x361f3b64,0x3b0eb78b,0xb872baa7,0xba2f3913,0xbb64361f,0x378b3b0e,0x3aa7b872,0xb913ba2f,
0x39a839a8,0x3872baa7,0xbb64b61f,0xb23e3bd9,0xb9a839a8,0x3aa73872,0x361fbb64,0xbbd9b23e,0x3b64361f,0x2e46bbf6,0xbbd9323e,0x378b3b0e,0xb61f3b64,0x3bf62e46,0xb23ebbd9,0xbb0e378b,
0x3c000000,0xb61fbb64,0xb9a839a8,0x3b64361f,0x80003c00,0x3b64b61f,0xb9a8b9a8,0xb61f3b64,0x3b64b61f,0xba2fb913,0xb23e3bd9,0x3ba8b4a5,0x361f3b64,0x3913ba2f,0xbbd9b23e,0x34a53ba8,
0x39a8b9a8,0xbbd9b23e,0x361f3b64,0x3872baa7,0x39a839a8,0x323ebbd9,0xbb64361f,0x3aa73872,0x361fbb64,0xbba834a5,0x3aa73872,0xae46bbf6,0x3b64361f,0xb4a5bba8,0xb8723aa7,0x3bf6ae46,
0xbc00,0xb9a839a8,0x3c000000,0xb9a8b9a8,0x3c000000,0xb9a8b9a8,0x80003c00,0x39a8b9a8,0xb61fbb64,0xb4a53ba8,0x3aa7b872,0xbbf6ae46,0x3b64b61f,0xbba8b4a5,0x38723aa7,0x2e46bbf6,
0xb9a8b9a8,0x323e3bd9,0x361fbb64,0xbaa73872,0x39a8b9a8,0xbbd9323e,0x3b64361f,0xb872baa7,0xbb64b61f,0x39133a2f,0xb23ebbd9,0xb4a53ba8,0x361fbb64,0xba2f3913,0x3bd9b23e,0xbba8b4a5,
0xbc008000,0x3b64361f,0xb9a8b9a8,0x361f3b64,0xbc00,0xb61f3b64,0x39a8b9a8,0xbb64361f,0xbb64361f,0x3bf6ae46,0xbbd9b23e,0x3b0e378b,0xb61fbb64,0x2e463bf6,0x323ebbd9,0xb78b3b0e,
0xb9a839a8,0x3aa7b872,0xbb64361f,0x3bd9b23e,0xb9a8b9a8,0x38723aa7,0xb61fbb64,0x323e3bd9,0xb61f3b64,0x378bbb0e,0xb8723aa7,0x3913ba2f,0xbb64b61f,0x3b0e378b,0xbaa7b872,0x3a2f3913,
0x3c00,0x3c000000,0xbc00,0xbc008000,0xbc000000,0x80003c00,0x3c000000,0xbc00,0x39a839a8,0x3913ba2f,0xbaa7b872,0xb78b3b0e,0xb9a839a8,0x3a2f3913,0x3872baa7,0xbb0eb78b,
0x3c000000,0xb23ebbd9,0xbb64361f,0x38723aa7,0x80003c00,0x3bd9b23e,0xb61fbb64,0xbaa73872,0x39a8b9a8,0xbb0eb78b,0xb23e3bd9,0x3bf6ae46,0x39a839a8,0x378bbb0e,0xbbd9b23e,0x2e463bf6,
0xbc00,0xbb64361f,0x39a839a8,0x361fbb64,0x3c000000,0xb61fbb64,0xb9a839a8,0x3b64361f,0xb9a8b9a8,0xb4a53ba8,0x3bd9b23e,0xb913ba2f,0x39a8b9a8,0xbba8b4a5,0x323e3bd9,0x3a2fb913,
0xbc008000,0x38723aa7,0x361fbb64,0xbbd9323e,0xbc00,0xbaa73872,0x3b64361f,0xb23ebbd9,0xb9a839a8,0x3bf62e46,0xb872baa7,0xb4a53ba8,0xb9a8b9a8,0xae463bf6,0x3aa7b872,0xbba8b4a5,
0x3c00,0x39a8b9a8,0xbc008000,0x39a839a8,0xbc000000,0x39a839a8,0xbc00,0xb9a839a8,0x39a839a8,0xae46bbf6,0xb8723aa7,0x3ba8b4a5,0xb9a839a8,0x3bf6ae46,0xbaa7b872,0x34a53ba8,
0x3c000000,0xbaa7b872,0x361f3b64,0x323ebbd9,0x80003c00,0x3872baa7,0xbb64361f,0x3bd9323e,0x39a8b9a8,0xbba834a5,0x3bd9323e,0xba2fb913,0x39a839a8,0xb4a5bba8,0xb23e3bd9,0x3913ba2f,
0xbc00,0xb61f3b64,0x39a8b9a8,0xbb64361f,0x3c000000,0xbb64b61f,0x39a839a8,0xb61fbb64,0xb9a8b9a8,0x378b3b0e,0xb23ebbd9,0xae463bf6,0x39a8b9a8,0xbb0e378b,0x3bd9b23e,0xbbf6ae46,
0xbc008000,0x3bd9323e,0xbb64b61f,0x3aa73872,0xbc00,0xb23e3bd9,0x361fbb64,0xb8723aa7,0xb9a839a8,0x3a2fb913,0xbaa73872,0x3b0eb78b,0xb9a8b9a8,0x39133a2f,0xb872baa7,0x378b3b0e,
0x3c00,0x3c000000,0xbc00,0xbc008000,0xbc000000,0x80003c00,0x3c000000,0xbc00,0x3b64361f,0x34a5bba8,0xbbd9b23e,0xae463bf6,0xb61f3b64,0x3ba834a5,0x323ebbd9,0xbbf6ae46,
0x39a8b9a8,0xbaa7b872,0xb61f3b64,0x3bd9323e,0x39a839a8,0x3872baa7,0xbb64b61f,0xb23e3bd9,0xb61fbb64,0xba2f3913,0x3aa73872,0x34a5bba8,0x3b64b61f,0xb913ba2f,0xb8723aa7,0x3ba834a5,
0xbc008000,0x361f3b64,0x39a8b9a8,0xbb64b61f,0xbc00,0xbb64361f,0x39a839a8,0x361fbb64,0xb61f3b64,0x3bf6ae46,0xb872baa7,0xb78b3b0e,0xbb64b61f,0x2e463bf6,0x3aa7b872,0xbb0eb78b,
0x39a839a8,0x323ebbd9,0xbb64361f,0x3aa73872,0xb9a839a8,0x3bd9323e,0xb61fbb64,0xb8723aa7,0x3b64b61f,0xbb0eb78b,0x323e3bd9,0x3913ba2f,0x361f3b64,0x378bbb0e,0xbbd9323e,0x3a2f3913,
0xbc00,0xb9a839a8,0x3c000000,0xb9a8b9a8,0x3c000000,0xb9a8b9a8,0x80003c00,0x39a8b9a8,0xbb64b61f,0x378b3b0e,0x323ebbd9,0xba2f3913,0x361fbb64,0xbb0e378b,0x3bd9323e,0xb913ba2f,
0xb9a839a8,0x3bd9b23e,0xbb64b61f,0x38723aa7,0xb9a8b9a8,0x323e3bd9,0x361fbb64,0xbaa73872,0x361f3b64,0x2e46bbf6,0xb8723aa7,0x3b0eb78b,0xbb64361f,0x3bf62e46,0xbaa7b872,0x378b3b0e,
0x3c000000,0xbb64b61f,0x39a839a8,0xb61fbb64,0x80003c00,0x361fbb64,0xb9a839a8,0x3b64b61f,0x361fbb64,0xb9133a2f,0x3aa7b872,0xbba834a5,0x3b64361f,0xba2fb913,0x38723aa7,0xb4a5bba8,
0xb9a8b9a8,0x38723aa7,0xb61fbb64,0x323e3bd9,0x39a8b9a8,0xbaa73872,0x3b64b61f,0xbbd9323e,0xbb64361f,0x3ba8b4a5,0xbbd9323e,0x3bf6ae46,0xb61fbb64,0x34a53ba8,0xb23ebbd9,0x2e463bf6,
0x3c00,0x3c000000,0xbc00,0xbc008000,0xbc000000,0x80003c00,0x3c000000,0xbc00,0x3c000000,0xae46bbf6,0xbbd9323e,0x34a53ba8,0x80003c00,0x3bf6ae46,0xb23ebbd9,0xbba834a5,
0xbc00,0xbbd9323e,0x361f3b64,0x3aa7b872,0x3c000000,0xb23ebbd9,0xbb64361f,0x38723aa7,0xbc008000,0x34a53ba8,0x3aa7b872,0xba2fb913,0xbc00,0xbba834a5,0x38723aa7,0x3913ba2f,
0x3c00,0x3b64b61f,0xb9a8b9a8,0xb61f3b64,0xbc000000,0x361f3b64,0x39a8b9a8,0xbb64b61f,0x3c000000,0xb78bbb0e,0xb8723aa7,0x3bf62e46,0x80003c00,0x3b0eb78b,0xbaa7b872,0xae463bf6,
0xbc00,0xbaa73872,0x3b64361f,0xb23ebbd9,0x3c000000,0xb872baa7,0xb61f3b64,0x3bd9b23e,0xbc008000,0x39133a2f,0x323ebbd9,0xbb0e378b,0xbc00,0xba2f3913,0x3bd9323e,0xb78bbb0e,
0x3c00,0x39a8b9a8,0xbc008000,0x39a839a8,0xbc000000,0x39a839a8,0xbc00,0xb9a839a8,0x3c000000,0xba2fb913,0x323e3bd9,0x378bbb0e,0x80003c00,0x3913ba2f,0xbbd9323e,0x3b0e378b,
0xbc00,0xb8723aa7,0x3b64b61f,0xbbd9b23e,0x3c000000,0xbaa7b872,0x361f3b64,0x323ebbd9,0xbc008000,0x3b0e378b,0xb872baa7,0x2e463bf6,0xbc00,0xb78b3b0e,0x3aa7b872,0xbbf62e46,
0x3c00,0x361fbb64,0xb9a839a8,0x3b64b61f,0xbc000000,0x3b64361f,0xb9a8b9a8,0x361f3b64,0x3c000000,0xbba8b4a5,0x3aa73872,0xb913ba2f,0x80003c00,0x34a5bba8,0xb8723aa7,0x3a2fb913,
0xbc00,0xb23e3bd9,0x361fbb64,0xb8723aa7,0x3c000000,0xbbd9b23e,0x3b64361f,0xbaa7b872,0xbc008000,0x3bf62e46,0xbbd9b23e,0x3ba834a5,0xbc00,0xae463bf6,0x323ebbd9,0xb4a53ba8,
0x3c00,0x3c000000,0xbc00,0xbc008000,0xbc000000,0x80003c00,0x3c000000,0xbc00,0x3b64b61f,0xb78bbb0e,0xbaa73872,0x39133a2f,0x361f3b64,0x3b0eb78b,0xb872baa7,0xba2f3913,
0xb9a8b9a8,0xb8723aa7,0x3b64361f,0x323ebbd9,0x39a8b9a8,0xbaa7b872,0xb61f3b64,0x3bd9323e,0xb61f3b64,0x3bf62e46,0xb23ebbd9,0xbb0e378b,0xbb64b61f,0xae463bf6,0x3bd9b23e,0xb78bbb0e,
0x3c000000,0xb61fbb64,0xb9a839a8,0x3b64361f,0x80003c00,0x3b64b61f,0xb9a8b9a8,0xb61f3b64,0xb61fbb64,0xb9133a2f,0x3bd9323e,0xb4a5bba8,0x3b64b61f,0xba2fb913,0xb23e3bd9,0x3ba8b4a5,
0xb9a839a8,0x3bd9323e,0xb61fbb64,0xb8723aa7,0xb9a8b9a8,0xb23e3bd9,0x3b64b61f,0xbaa7b872,0x3b64361f,0xb4a5bba8,0xb8723aa7,0x3bf6ae46,0xb61f3b64,0x3ba8b4a5,0xbaa7b872,0x2e463bf6,
0xbc00,0xb9a839a8,0x3c000000,0xb9a8b9a8,0x3c000000,0xb9a8b9a8,0x80003c00,0x39a8b9a8,0xbb64361f,0x3ba834a5,0xb872baa7,0xae463bf6,0xb61fbb64,0xb4a53ba8,0x3aa7b872,0xbbf6ae46,
0x39a839a8,0xb23ebbd9,0xb61f3b64,0x3aa7b872,0xb9a839a8,0x3bd9b23e,0xbb64b61f,0x38723aa7,0x361fbb64,0xba2f3913,0x3bd9b23e,0xbba8b4a5,0x3b64361f,0xb913ba2f,0x323e3bd9,0x34a5bba8,
0xbc008000,0x3b64361f,0xb9a8b9a8,0x361f3b64,0xbc00,0xb61f3b64,0x39a8b9a8,0xbb64361f,0x361f3b64,0xae46bbf6,0xb23e3bd9,0x378bbb0e,0xbb64361f,0x3bf6ae46,0xbbd9b23e,0x3b0e378b,
0x39a8b9a8,0xbaa73872,0x3b64b61f,0xbbd9323e,0x39a839a8,0xb872baa7,0x361f3b64,0xb23ebbd9,0xbb64b61f,0x3b0e378b,0xbaa7b872,0x3a2f3913,0x361fbb64,0xb78b3b0e,0x3872baa7,0xb9133a2f,
0x3c00,0x3c000000,0xbc00,0xbc008000,0xbc000000,0x80003c00,0x3c000000,0xbc00,0x39a8b9a8,0xba2fb913,0xb8723aa7,0x3b0e378b,0x39a839a8,0x3913ba2f,0xbaa7b872,0xb78b3b0e,
0xbc008000,0x323e3bd9,0x3b64b61f,0xb872baa7,0xbc00,0xbbd9323e,0x361f3b64,0x3aa7b872,0x39a839a8,0x378bbb0e,0xbbd9b23e,0x2e463bf6,0xb9a839a8,0x3b0e378b,0x323ebbd9,0xbbf62e46,
0xbc00,0xbb64361f,0x39a839a8,0x361fbb64,0x3c000000,0xb61fbb64,0xb9a839a8,0x3b64361f,0xb9a839a8,0x3ba834a5,0xb23ebbd9,0xba2f3913,0xb9a8b9a8,0xb4a53ba8,0x3bd9b23e,0xb913ba2f,
0x3c000000,0xb872baa7,0xb61f3b64,0x3bd9b23e,0x80003c00,0x3aa7b872,0xbb64b61f,0x323e3bd9,0xb9a8b9a8,0xae463bf6,0x3aa7b872,0xbba8b4a5,0x39a8b9a8,0xbbf6ae46,0x38723aa7,0x34a5bba8,
0x3c00,0x39a8b9a8,0xbc008000,0x39a839a8,0xbc000000,0x39a839a8,0xbc00,0xb9a839a8,0x39a8b9a8,0xbbf62e46,0x3aa73872,0xb4a5bba8,0x39a839a8,0xae46bbf6,0xb8723aa7,0x3ba8b4a5,
0xbc008000,0x3aa73872,0xb61fbb64,0xb23e3bd9,0xbc00,0xb8723aa7,0x3b64b61f,0xbbd9b23e,0x39a839a8,0xb4a5bba8,0xb23e3bd9,0x3913ba2f,0xb9a839a8,0x3ba8b4a5,0xbbd9b23e,0x3a2f3913,
0xbc00,0xb61f3b64,0x39a8b9a8,0xbb64361f,0x3c000000,0xbb64b61f,0x39a839a8,0xb61fbb64,0xb9a839a8,0x3b0eb78b,0xbbd9323e,0x3bf62e46,0xb9a8b9a8,0x378b3b0e,0xb23ebbd9,0xae463bf6,
0x3c000000,0xbbd9b23e,0x3b64361f,0xbaa7b872,0x80003c00,0x323ebbd9,0xb61f3b64,0x3872baa7,0xb9a8b9a8,0x39133a2f,0xb872baa7,0x378b3b0e,0x39a8b9a8,0xba2f3913,0x3aa7b872,0xbb0e378b,
0x3c00,0x3c000000,0xbc00,0xbc008000,0xbc000000,0x80003c00,0x3c000000,0xbc00,0x361fbb64,0xbba8b4a5,0xb23e3bd9,0x3bf62e46,0x3b64361f,0x34a5bba8,0xbbd9b23e,0xae463bf6,
0xb9a839a8,0x3aa73872,0x361fbb64,0xbbd9b23e,0xb9a8b9a8,0xb8723aa7,0x3b64361f,0x323ebbd9,0x3b64b61f,0xb913ba2f,0xb8723aa7,0x3ba834a5,0x361f3b64,0x3a2fb913,0xbaa7b872,0xb4a53ba8,
0xbc008000,0x361f3b64,0x39a8b9a8,0xbb64b61f,0xbc00,0xbb64361f,0x39a839a8,0x361fbb64,0x3b64361f,0xae46bbf6,0xbaa73872,0x3b0e378b,0xb61f3b64,0x3bf6ae46,0xb872baa7,0xb78b3b0e,
0xb9a8b9a8,0xb23e3bd9,0x3b64b61f,0xbaa7b872,0x39a8b9a8,0xbbd9b23e,0x361f3b64,0x3872baa7,0x361f3b64,0x378bbb0e,0xbbd9323e,0x3a2f3913,0xbb64361f,0x3b0e378b,0xb23ebbd9,0xb9133a2f,
0xbc00,0xb9a839a8,0x3c000000,0xb9a8b9a8,0x3c000000,0xb9a8b9a8,0x80003c00,0x39a8b9a8,0xb61f3b64,0x3b0eb78b,0xbbd9b23e,0x39133a2f,0xbb64b61f,0x378b3b0e,0x323ebbd9,0xba2f3913,
0x39a8b9a8,0xbbd9323e,0x3b64361f,0xb872baa7,0x39a839a8,0xb23ebbd9,0xb61f3b64,0x3aa7b872,0xbb64361f,0x3bf62e46,0xbaa7b872,0x378b3b0e,0xb61fbb64,0xae463bf6,0x3872baa7,0xbb0e378b,
0x3c000000,0xbb64b61f,0x39a839a8,0xb61fbb64,0x80003c00,0x361fbb64,0xb9a839a8,0x3b64b61f,0xbb64b61f,0x3a2f3913,0xb872baa7,0x34a53ba8,0x361fbb64,0xb9133a2f,0x3aa7b872,0xbba834a5,
0x39a839a8,0xb872baa7,0x361f3b64,0xb23ebbd9,0xb9a839a8,0x3aa7b872,0xbb64361f,0x3bd9b23e,0xb61fbb64,0x34a53ba8,0xb23ebbd9,0x2e463bf6,0x3b64b61f,0xbba834a5,0x3bd9b23e,0xbbf62e46,
0x80003c00,0xbc000000,0x8000bc00,0x3c008000,0x3c000000,0x3c00,0xbc000000,0x8000bc00,0x8000bc00,0x3bf62e46,0xb23e3bd9,0xbba8b4a5,0xbc000000,0x2e46bbf6,0x3bd9323e,0xb4a53ba8,
0x80003c00,0xbbd9b23e,0x361fbb64,0x3aa73872,0x3c000000,0xb23e3bd9,0xbb64b61f,0x3872baa7,0x8000bc00,0x3ba834a5,0xb8723aa7,0xb913ba2f,0xbc000000,0x34a5bba8,0x3aa73872,0xba2f3913,
0x80003c00,0xbb64b61f,0x39a8b9a8,0x361f3b64,0x3c000000,0xb61f3b64,0xb9a8b9a8,0x3b64b61f,0x8000bc00,0x3b0e378b,0xbaa73872,0xae46bbf6,0xbc000000,0x378bbb0e,0x38723aa7,0xbbf62e46,
0x80003c00,0xbaa7b872,0x3b64b61f,0xb23e3bd9,0x3c000000,0xb8723aa7,0xb61fbb64,0x3bd9323e,0x8000bc00,0x3a2f3913,0xbbd9323e,0x378bbb0e,0xbc000000,0x3913ba2f,0x323e3bd9,0xbb0eb78b,
0x80003c00,0xb9a8b9a8,0x3c008000,0xb9a839a8,0x3c000000,0xb9a839a8,0x8000bc00,0x39a839a8,0x8000bc00,0x39133a2f,0xbbd9b23e,0x3b0eb78b,0xbc000000,0x3a2fb913,0xb23e3bd9,0xb78bbb0e,
0x80003c00,0xb872baa7,0x3b64361f,0xbbd9323e,0x3c000000,0xbaa73872,0x361fbb64,0x323e3bd9,0x8000bc00,0x378b3b0e,0xbaa7b872,0x3bf62e46,0xbc000000,0x3b0eb78b,0xb8723aa7,0x2e46bbf6,
0x80003c00,0xb61fbb64,0x39a839a8,0xbb64b61f,0x3c000000,0xbb64361f,0x39a8b9a8,0xb61f3b64,0x8000bc00,0x34a53ba8,0xb872baa7,0x3a2f3913,0xbc000000,0x3ba8b4a5,0xbaa73872,0x3913ba2f,
0x80003c00,0xb23ebbd9,0x361f3b64,0xb872baa7,0x3c000000,0xbbd9323e,0x3b64b61f,0xbaa73872,0x8000bc00,0x2e463bf6,0xb23ebbd9,0x34a53ba8,0xbc000000,0x3bf6ae46,0xbbd9323e,0x3ba8b4a5,
0x80003c00,0xbc000000,0x8000bc00,0x3c008000,0x3c000000,0x3c00,0xbc000000,0x8000bc00,0x361fbb64,0x3b0e378b,0xb8723aa7,0xba2fb913,0xbb64b61f,0x378bbb0e,0x3aa73872,0xb9133a2f,
0xb9a839a8,0xb872baa7,0x3b64b61f,0x323e3bd9,0x39a839a8,0xbaa73872,0xb61fbb64,0x3bd9b23e,0x3b64b61f,0x2e463bf6,0xbbd9b23e,0x378bbb0e,0xb61fbb64,0x3bf6ae46,0xb23e3bd9,0xbb0eb78b,
0xbc000000,0x361fbb64,0x39a839a8,0xbb64361f,0x3c00,0xbb64b61f,0x39a8b9a8,0x361f3b64,0x3b64361f,0xba2f3913,0xb23ebbd9,0x3ba834a5,0x361fbb64,0x39133a2f,0xbbd9323e,0x34a5bba8,
0xb9a8b9a8,0x3bd9b23e,0xb61f3b64,0xb872baa7,0xb9a839a8,0xb23ebbd9,0x3b64361f,0xbaa73872,0x361f3b64,0xbba8b4a5,0x3aa7b872,0xae463bf6,0x3b64b61f,0xb4a53ba8,0xb872baa7,0x3bf62e46,
0x8000bc00,0x39a839a8,0xbc000000,0x39a8b9a8,0xbc000000,0x39a8b9a8,0x3c00,0xb9a8b9a8,0xb61f3b64,0xb4a5bba8,0x3aa73872,0xbbf62e46,0x3b64361f,0xbba834a5,0x3872baa7,0x2e463bf6,
0x39a8b9a8,0xb23e3bd9,0xb61fbb64,0x3aa73872,0xb9a8b9a8,0x3bd9323e,0xbb64361f,0x3872baa7,0xbb64361f,0x3913ba2f,0xb23e3bd9,0xb4a5bba8,0x361f3b64,0xba2fb913,0x3bd9323e,0xbba834a5,
0x3c008000,0xbb64361f,0x39a8b9a8,0xb61f3b64,0x8000bc00,0x361f3b64,0xb9a8b9a8,0x3b64361f,0xbb64b61f,0x3bf62e46,0xbbd9323e,0x3b0eb78b,0xb61f3b64,0x2e46bbf6,0x323e3bd9,0xb78bbb0e,
0x39a839a8,0xbaa7b872,0x3b64361f,0xbbd9b23e,0x39a8b9a8,0xb8723aa7,0x361fbb64,0xb23e3bd9,0xb61fbb64,0x378b3b0e,0xb872baa7,0x39133a2f,0xbb64361f,0x3b0eb78b,0xbaa73872,0x3a2fb913,
0x80003c00,0xbc000000,0x8000bc00,0x3c008000,0x3c000000,0x3c00,0xbc000000,0x8000bc00,0x39a8b9a8,0x39133a2f,0xbaa73872,0xb78bbb0e,0xb9a8b9a8,0x3a2fb913,0x38723aa7,0xbb0e378b,
0xbc000000,0x323ebbd9,0x3b64361f,0xb8723aa7,0x3c00,0xbbd9b23e,0x361fbb64,0x3aa73872,0x39a839a8,0xbb0e378b,0xb23ebbd9,0x3bf62e46,0x39a8b9a8,0x378b3b0e,0xbbd9323e,0x2e46bbf6,
0x8000bc00,0x3b64361f,0xb9a839a8,0xb61fbb64,0xbc000000,0x361fbb64,0x39a839a8,0xbb64361f,0xb9a839a8,0xb4a5bba8,0x3bd9323e,0xb9133a2f,0x39a839a8,0xbba834a5,0x323ebbd9,0x3a2f3913,
0x3c008000,0xb8723aa7,0xb61fbb64,0x3bd9323e,0x8000bc00,0x3aa73872,0xbb64361f,0x323ebbd9,0xb9a8b9a8,0x3bf6ae46,0xb8723aa7,0xb4a5bba8,0xb9a839a8,0xae46bbf6,0x3aa73872,0xbba834a5,
0x80003c00,0xb9a8b9a8,0x3c008000,0xb9a839a8,0x3c000000,0xb9a839a8,0x8000bc00,0x39a839a8,0x39a8b9a8,0xae463bf6,0xb872baa7,0x3ba834a5,0xb9a8b9a8,0x3bf62e46,0xbaa73872,0x34a5bba8,
0xbc000000,0x3aa7b872,0xb61f3b64,0xb23ebbd9,0x3c00,0xb872baa7,0x3b64361f,0xbbd9323e,0x39a839a8,0xbba8b4a5,0x3bd9b23e,0xba2f3913,0x39a8b9a8,0xb4a53ba8,0xb23ebbd9,0x39133a2f,
0x8000bc00,0x361f3b64,0xb9a8b9a8,0x3b64361f,0xbc000000,0x3b64b61f,0xb9a839a8,0x361fbb64,0xb9a839a8,0x378bbb0e,0xb23e3bd9,0xae46bbf6,0x39a839a8,0xbb0eb78b,0x3bd9323e,0xbbf62e46,
0x3c008000,0xbbd9323e,0x3b64b61f,0xbaa73872,0x8000bc00,0x323e3bd9,0xb61fbb64,0x38723aa7,0xb9a8b9a8,0x3a2f3913,0xbaa7b872,0x3b0e378b,0xb9a839a8,0x3913ba2f,0xb8723aa7,0x378bbb0e,
0x80003c00,0xbc000000,0x8000bc00,0x3c008000,0x3c000000,0x3c00,0xbc000000,0x8000bc00,0x3b64b61f,0x34a53ba8,0xbbd9323e,0xae46bbf6,0xb61fbb64,0x3ba8b4a5,0x323e3bd9,0xbbf62e46,
0xb9a8b9a8,0x3aa7b872,0x361f3b64,0xbbd9323e,0xb9a839a8,0xb872baa7,0x3b64b61f,0x323e3bd9,0xb61f3b64,0xba2fb913,0x3aa7b872,0x34a53ba8,0x3b64361f,0xb9133a2f,0xb872baa7,0x3ba8b4a5,
0x3c008000,0xb61f3b64,0xb9a8b9a8,0x3b64b61f,0x8000bc00,0x3b64361f,0xb9a839a8,0xb61fbb64,0xb61fbb64,0x3bf62e46,0xb8723aa7,0xb78bbb0e,0xbb64361f,0x2e46bbf6,0x3aa73872,0xbb0e378b,
0xb9a839a8,0xb23ebbd9,0x3b64361f,0xbaa73872,0x39a839a8,0xbbd9323e,0x361fbb64,0x38723aa7,0x3b64361f,0xbb0e378b,0x323ebbd9,0x39133a2f,0x361fbb64,0x378b3b0e,0xbbd9b23e,0x3a2fb913,
0x8000bc00,0x39a839a8,0xbc000000,0x39a8b9a8,0xbc000000,0x39a8b9a8,0x3c00,0xb9a8b9a8,0xbb64361f,0x378bbb0e,0x323e3bd9,0xba2fb913,0x361f3b64,0xbb0eb78b,0x3bd9b23e,0xb9133a2f,
0x39a839a8,0xbbd9b23e,0x3b64b61f,0xb8723aa7,0x39a8b9a8,0xb23e3bd9,0xb61fbb64,0x3aa73872,0x361fbb64,0x2e463bf6,0xb872baa7,0x3b0e378b,0xbb64b61f,0x3bf6ae46,0xbaa73872,0x378bbb0e,
0xbc000000,0x3b64b61f,0xb9a839a8,0x361fbb64,0x3c00,0xb61fbb64,0x39a839a8,0xbb64b61f,0x361f3b64,0xb913ba2f,0x3aa73872,0xbba8b4a5,0x3b64b61f,0xba2f3913,0x3872baa7,0xb4a53ba8,
0x39a8b9a8,0xb8723aa7,0x361fbb64,0xb23e3bd9,0xb9a8b9a8,0x3aa73872,0xbb64b61f,0x3bd9323e,0xbb64b61f,0x3ba834a5,0xbbd9b23e,0x3bf62e46,0xb61f3b64,0x34a5bba8,0xb23e3bd9,0x2e46bbf6,
0x80003c00,0xbc000000,0x8000bc00,0x3c008000,0x3c000000,0x3c00,0xbc000000,0x8000bc00,0x3c008000,0xae463bf6,0xbbd9b23e,0x34a5bba8,0x8000bc00,0x3bf62e46,0xb23e3bd9,0xbba8b4a5,
0x8000bc00,0x3bd9323e,0xb61f3b64,0xbaa7b872,0xbc000000,0x323ebbd9,0x3b64361f,0xb8723aa7,0xbc000000,0x34a5bba8,0x3aa73872,0xba2f3913,0x3c00,0xbba8b4a5,0x3872baa7,0x39133a2f,
0x80003c00,0xbb64b61f,0x39a8b9a8,0x361f3b64,0x3c000000,0xb61f3b64,0xb9a8b9a8,0x3b64b61f,0x3c008000,0xb78b3b0e,0xb872baa7,0x3bf6ae46,0x8000bc00,0x3b0e378b,0xbaa73872,0xae46bbf6,
0x8000bc00,0x3aa73872,0xbb64361f,0x323ebbd9,0xbc000000,0x3872baa7,0x361f3b64,0xbbd9b23e,0xbc000000,0x3913ba2f,0x323e3bd9,0xbb0eb78b,0x3c00,0xba2fb913,0x3bd9b23e,0xb78b3b0e,
0x80003c00,0xb9a8b9a8,0x3c008000,0xb9a839a8,0x3c000000,0xb9a839a8,0x8000bc00,0x39a839a8,0x3c008000,0xba2f3913,0x323ebbd9,0x378b3b0e,0x8000bc00,0x39133a2f,0xbbd9b23e,0x3b0eb78b,
0x8000bc00,0x38723aa7,0xbb64b61f,0x3bd9b23e,0xbc000000,0x3aa7b872,0xb61f3b64,0xb23ebbd9,0xbc000000,0x3b0eb78b,0xb8723aa7,0x2e46bbf6,0x3c00,0xb78bbb0e,0x3aa73872,0xbbf6ae46,
0x80003c00,0xb61fbb64,0x39a839a8,0xbb64b61f,0x3c000000,0xbb64361f,0x39a8b9a8,0xb61f3b64,0x3c008000,0xbba834a5,0x3aa7b872,0xb9133a2f,0x8000bc00,0x34a53ba8,0xb872baa7,0x3a2f3913,
0x8000bc00,0x323e3bd9,0xb61fbb64,0x38723aa7,0xbc000000,0x3bd9b23e,0xbb64361f,0x3aa7b872,0xbc000000,0x3bf6ae46,0xbbd9323e,0x3ba8b4a5,0x3c00,0xae46bbf6,0x323e3bd9,0xb4a5bba8,
0x80003c00,0xbc000000,0x8000bc00,0x3c008000,0x3c000000,0x3c00,0xbc000000,0x8000bc00,0x3b64361f,0xb78b3b0e,0xbaa7b872,0x3913ba2f,0x361fbb64,0x3b0e378b,0xb8723aa7,0xba2fb913,
0x39a8b9a8,0x38723aa7,0xbb64361f,0xb23ebbd9,0xb9a8b9a8,0x3aa7b872,0x361f3b64,0xbbd9323e,0xb61fbb64,0x3bf6ae46,0xb23e3bd9,0xbb0eb78b,0xbb64361f,0xae46bbf6,0x3bd9323e,0xb78b3b0e,
0xbc000000,0x361fbb64,0x39a839a8,0xbb64361f,0x3c00,0xbb64b61f,0x39a8b9a8,0x361f3b64,0xb61f3b64,0xb913ba2f,0x3bd9b23e,0xb4a53ba8,0x3b64361f,0xba2f3913,0xb23ebbd9,0x3ba834a5,
0x39a839a8,0xbbd9323e,0x361fbb64,0x38723aa7,0x39a8b9a8,0x323e3bd9,0xbb64b61f,0x3aa7b872,0x3b64b61f,0xb4a53ba8,0xb872baa7,0x3bf62e46,0xb61fbb64,0x3ba834a5,0xbaa73872,0x2e46bbf6,
0x8000bc00,0x39a839a8,0xbc000000,0x39a8b9a8,0xbc000000,0x39a8b9a8,0x3c00,0xb9a8b9a8,0xbb64b61f,0x3ba8b4a5,0xb8723aa7,0xae46bbf6,0xb61f3b64,0xb4a5bba8,0x3aa73872,0xbbf62e46,
0xb9a839a8,0x323ebbd9,0x361f3b64,0xbaa7b872,0x39a839a8,0xbbd9b23e,0x3b64b61f,0xb8723aa7,0x361f3b64,0xba2fb913,0x3bd9323e,0xbba834a5,0x3b64b61f,0xb9133a2f,0x323ebbd9,0x34a53ba8,
0x3c008000,0xbb64361f,0x39a8b9a8,0xb61f3b64,0x8000bc00,0x361f3b64,0xb9a8b9a8,0x3b64361f,0x361fbb64,0xae463bf6,0xb23ebbd9,0x378b3b0e,0xbb64b61f,0x3bf62e46,0xbbd9323e,0x3b0eb78b,
0xb9a8b9a8,0x3aa73872,0xbb64b61f,0x3bd9323e,0xb9a839a8,0x3872baa7,0xb61f3b64,0x323ebbd9,0xbb64361f,0x3b0eb78b,0xbaa73872,0x3a2fb913,0x361f3b64,0xb78bbb0e,0x38723aa7,0xb913ba2f,
0x80003c00,0xbc000000,0x8000bc00,0x3c008000,0x3c000000,0x3c00,0xbc000000,0x8000bc00,0x39a839a8,0xba2f3913,0xb872baa7,0x3b0eb78b,0x39a8b9a8,0x39133a2f,0xbaa73872,0xb78bbb0e,
0x3c008000,0xb23e3bd9,0xbb64b61f,0x3872baa7,0x8000bc00,0x3bd9323e,0xb61f3b64,0xbaa7b872,0x39a8b9a8,0x378b3b0e,0xbbd9323e,0x2e46bbf6,0xb9a8b9a8,0x3b0eb78b,0x323e3bd9,0xbbf6ae46,
0x8000bc00,0x3b64361f,0xb9a839a8,0xb61fbb64,0xbc000000,0x361fbb64,0x39a839a8,0xbb64361f,0xb9a8b9a8,0x3ba8b4a5,0xb23e3bd9,0xba2fb913,0xb9a839a8,0xb4a5bba8,0x3bd9323e,0xb9133a2f,
0xbc000000,0x3872baa7,0x361f3b64,0xbbd9b23e,0x3c00,0xbaa7b872,0x3b64b61f,0xb23e3bd9,0xb9a839a8,0xae46bbf6,0x3aa73872,0xbba834a5,0x39a839a8,0xbbf62e46,0x3872baa7,0x34a53ba8,
0x80003c00,0xb9a8b9a8,0x3c008000,0xb9a839a8,0x3c000000,0xb9a839a8,0x8000bc00,0x39a839a8,0x39a839a8,0xbbf6ae46,0x3aa7b872,0xb4a53ba8,0x39a8b9a8,0xae463bf6,0xb872baa7,0x3ba834a5,
0x3c008000,0xbaa73872,0x361fbb64,0x323e3bd9,0x8000bc00,0x38723aa7,0xbb64b61f,0x3bd9b23e,0x39a8b9a8,0xb4a53ba8,0xb23ebbd9,0x39133a2f,0xb9a8b9a8,0x3ba834a5,0xbbd9323e,0x3a2fb913,
0x8000bc00,0x361f3b64,0xb9a8b9a8,0x3b64361f,0xbc000000,0x3b64b61f,0xb9a839a8,0x361fbb64,0xb9a8b9a8,0x3b0e378b,0xbbd9b23e,0x3bf6ae46,0xb9a839a8,0x378bbb0e,0xb23e3bd9,0xae46bbf6,
0xbc000000,0x3bd9b23e,0xbb64361f,0x3aa7b872,0x3c00,0xb23ebbd9,0x361f3b64,0xb872baa7,0xb9a839a8,0x3913ba2f,0xb8723aa7,0x378bbb0e,0x39a839a8,0xba2fb913,0x3aa73872,0xbb0eb78b,
0x80003c00,0xbc000000,0x8000bc00,0x3c008000,0x3c000000,0x3c00,0xbc000000,0x8000bc00,0x361f3b64,0xbba834a5,0xb23ebbd9,0x3bf6ae46,0x3b64b61f,0x34a53ba8,0xbbd9323e,0xae46bbf6,
0x39a839a8,0xbaa73872,0xb61fbb64,0x3bd9b23e,0x39a8b9a8,0x38723aa7,0xbb64361f,0xb23ebbd9,0x3b64361f,0xb9133a2f,0xb872baa7,0x3ba8b4a5,0x361fbb64,0x3a2f3913,0xbaa73872,0xb4a5bba8,
0x3c008000,0xb61f3b64,0xb9a8b9a8,0x3b64b61f,0x8000bc00,0x3b64361f,0xb9a839a8,0xb61fbb64,0x3b64b61f,0xae463bf6,0xbaa7b872,0x3b0eb78b,0xb61fbb64,0x3bf62e46,0xb8723aa7,0xb78bbb0e,
0x39a8b9a8,0x323e3bd9,0xbb64b61f,0x3aa7b872,0xb9a8b9a8,0x3bd9b23e,0xb61f3b64,0xb872baa7,0x361fbb64,0x378b3b0e,0xbbd9b23e,0x3a2fb913,0xbb64b61f,0x3b0eb78b,0xb23e3bd9,0xb913ba2f,
0x8000bc00,0x39a839a8,0xbc000000,0x39a8b9a8,0xbc000000,0x39a8b9a8,0x3c00,0xb9a8b9a8,0xb61fbb64,0x3b0e378b,0xbbd9323e,0x3913ba2f,0xbb64361f,0x378bbb0e,0x323e3bd9,0xba2fb913,
0xb9a8b9a8,0x3bd9323e,0xbb64361f,0x3872baa7,0xb9a839a8,0x323ebbd9,0x361f3b64,0xbaa7b872,0xbb64b61f,0x3bf6ae46,0xbaa73872,0x378bbb0e,0xb61f3b64,0xae46bbf6,0x38723aa7,0xbb0eb78b,
0xbc000000,0x3b64b61f,0xb9a839a8,0x361fbb64,0x3c00,0xb61fbb64,0x39a839a8,0xbb64b61f,0xbb64361f,0x3a2fb913,0xb8723aa7,0x34a5bba8,0x361f3b64,0xb913ba2f,0x3aa73872,0xbba8b4a5,
0xb9a839a8,0x3872baa7,0xb61f3b64,0x323ebbd9,0x39a839a8,0xbaa7b872,0x3b64361f,0xbbd9b23e,0xb61f3b64,0x34a5bba8,0xb23e3bd9,0x2e46bbf6,0x3b64361f,0xbba8b4a5,0x3bd9323e,0xbbf6ae46,
0x3c00,0xbc00,0x3c00,0xbc00,0xbc000000,0x3c000000,0xbc000000,0x3c000000,0x3c00,0xae46bbf6,0x323e3bd9,0xb4a5bba8,0xbc000000,0x3bf6ae46,0xbbd9323e,0x3ba8b4a5,
0x3c00,0xb23ebbd9,0x361f3b64,0xb872baa7,0xbc000000,0x3bd9b23e,0xbb64361f,0x3aa7b872,0x3c00,0xb4a5bba8,0x38723aa7,0xba2fb913,0xbc000000,0x3ba8b4a5,0xbaa73872,0x3913ba2f,
0x3c00,0xb61fbb64,0x39a839a8,0xbb64b61f,0xbc000000,0x3b64b61f,0xb9a839a8,0x361fbb64,0x3c00,0xb78bbb0e,0x3aa73872,0xbbf6ae46,0xbc000000,0x3b0eb78b,0xb8723aa7,0x2e46bbf6,
0x3c00,0xb872baa7,0x3b64361f,0xbbd9323e,0xbc000000,0x3aa7b872,0xb61f3b64,0xb23ebbd9,0x3c00,0xb913ba2f,0x3bd9323e,0xbb0e378b,0xbc000000,0x3a2fb913,0xb23e3bd9,0xb78bbb0e,
0x3c00,0xb9a8b9a8,0x3c000000,0xb9a839a8,0xbc000000,0x39a8b9a8,0x80003c00,0xb9a8b9a8,0x3c00,0xba2fb913,0x3bd9b23e,0xb78b3b0e,0xbc000000,0x3913ba2f,0x323e3bd9,0xbb0eb78b,
0x3c00,0xbaa7b872,0x3b64b61f,0xb23e3bd9,0xbc000000,0x3872baa7,0x361f3b64,0xbbd9b23e,0x3c00,0xbb0eb78b,0x3aa7b872,0x2e463bf6,0xbc000000,0x378bbb0e,0x38723aa7,0xbbf62e46,
0x3c00,0xbb64b61f,0x39a8b9a8,0x361f3b64,0xbc000000,0x361fbb64,0x39a839a8,0xbb64361f,0x3c00,0xbba8b4a5,0x3872baa7,0x39133a2f,0xbc000000,0x34a5bba8,0x3aa73872,0xba2f3913,
0x3c00,0xbbd9b23e,0x361fbb64,0x3aa73872,0xbc000000,0x323ebbd9,0x3b64361f,0xb8723aa7,0x3c00,0xbbf6ae46,0x323ebbd9,0x3ba834a5,0xbc000000,0x2e46bbf6,0x3bd9323e,0xb4a53ba8,
0x3c00,0xbc00,0x3c00,0xbc00,0xbc000000,0x3c000000,0xbc000000,0x3c000000,0x361f3b64,0xb78bbb0e,0x38723aa7,0xb913ba2f,0xbb64361f,0x3b0eb78b,0xbaa73872,0x3a2fb913,
0x39a839a8,0xbaa7b872,0x3b64361f,0xbbd9b23e,0xb9a839a8,0x3872baa7,0xb61f3b64,0x323ebbd9,0x3b64361f,0xbbf6ae46,0x3bd9b23e,0xbb0e378b,0xb61f3b64,0x2e46bbf6,0x323e3bd9,0xb78bbb0e,
0x3c000000,0xbb64361f,0x39a8b9a8,0xb61f3b64,0x80003c00,0xb61fbb64,0x39a839a8,0xbb64b61f,0x3b64b61f,0xb9133a2f,0x323ebbd9,0x34a53ba8,0x361f3b64,0xba2fb913,0x3bd9323e,0xbba834a5,
0x39a8b9a8,0xb23e3bd9,0xb61fbb64,0x3aa73872,0x39a839a8,0xbbd9b23e,0x3b64b61f,0xb8723aa7,0x361fbb64,0x34a53ba8,0xbaa7b872,0x3bf6ae46,0x3b64361f,0xbba834a5,0x3872baa7,0x2e463bf6,
0xbc00,0x39a839a8,0xbc008000,0x39a8b9a8,0x3c000000,0xb9a839a8,0xbc00,0x39a839a8,0xb61fbb64,0x3ba834a5,0xbaa73872,0x2e46bbf6,0x3b64b61f,0xb4a53ba8,0xb872baa7,0x3bf62e46,
0xb9a8b9a8,0x3bd9b23e,0xb61f3b64,0xb872baa7,0x39a8b9a8,0x323e3bd9,0xbb64b61f,0x3aa7b872,0xbb64b61f,0x3a2fb913,0x323e3bd9,0xbba8b4a5,0x361fbb64,0x39133a2f,0xbbd9323e,0x34a5bba8,
0xbc008000,0x361fbb64,0x39a839a8,0xbb64361f,0xbc00,0x3b64361f,0xb9a839a8,0xb61fbb64,0xbb64361f,0xae46bbf6,0x3bd9323e,0xb78b3b0e,0xb61fbb64,0x3bf6ae46,0xb23e3bd9,0xbb0eb78b,
0xb9a839a8,0xb872baa7,0x3b64b61f,0x323e3bd9,0xb9a8b9a8,0x3aa7b872,0x361f3b64,0xbbd9323e,0xb61f3b64,0xbb0eb78b,0x3872baa7,0x3a2f3913,0xbb64b61f,0x378bbb0e,0x3aa73872,0xb9133a2f,
0x3c00,0xbc00,0x3c00,0xbc00,0xbc000000,0x3c000000,0xbc000000,0x3c000000,0x39a839a8,0xba2fb913,0x3aa73872,0xbb0eb78b,0xb9a839a8,0x3913ba2f,0xb8723aa7,0x378bbb0e,
0x3c000000,0xbbd9323e,0x3b64b61f,0xbaa73872,0x80003c00,0xb23ebbd9,0x361f3b64,0xb872baa7,0x39a8b9a8,0xb78b3b0e,0x323ebbd9,0x2e463bf6,0x39a839a8,0xbb0eb78b,0x3bd9323e,0xbbf62e46,
0xbc00,0x361f3b64,0xb9a8b9a8,0x3b64361f,0x3c000000,0xbb64361f,0x39a8b9a8,0xb61f3b64,0xb9a8b9a8,0x3ba834a5,0xbbd9323e,0x3a2fb913,0x39a8b9a8,0xb4a53ba8,0xb23ebbd9,0x39133a2f,
0xbc008000,0x3aa7b872,0xb61f3b64,0xb23ebbd9,0xbc00,0x38723aa7,0xbb64b61f,0x3bd9b23e,0xb9a839a8,0x2e46bbf6,0x38723aa7,0xbba8b4a5,0xb9a8b9a8,0x3bf62e46,0xbaa73872,0x34a5bba8,
0x3c00,0xb9a8b9a8,0x3c000000,0xb9a839a8,0xbc000000,0x39a8b9a8,0x80003c00,0xb9a8b9a8,0x39a839a8,0xbbf62e46,0x3872baa7,0x34a53ba8,0xb9a839a8,0xae46bbf6,0x3aa73872,0xbba834a5,
0x3c000000,0xb8723aa7,0xb61fbb64,0x3bd9323e,0x80003c00,0xbaa7b872,0x3b64b61f,0xb23e3bd9,0x39a8b9a8,0x34a53ba8,0xbbd9b23e,0x3913ba2f,0x39a839a8,0xbba834a5,0x323ebbd9,0x3a2f3913,
0xbc00,0x3b64361f,0xb9a839a8,0xb61fbb64,0x3c000000,0xb61f3b64,0xb9a8b9a8,0x3b64b61f,0xb9a8b9a8,0x3b0eb78b,0x323e3bd9,0xbbf6ae46,0x39a8b9a8,0x378b3b0e,0xbbd9323e,0x2e46bbf6,
0xbc008000,0x323ebbd9,0x3b64361f,0xb8723aa7,0xbc00,0x3bd9323e,0xb61f3b64,0xbaa7b872,0xb9a839a8,0xb913ba2f,0x3aa7b872,0x378b3b0e,0xb9a8b9a8,0x3a2fb913,0x38723aa7,0xbb0e378b,
0x3c00,0xbc00,0x3c00,0xbc00,0xbc000000,0x3c000000,0xbc000000,0x3c000000,0x3b64361f,0xbba8b4a5,0x3bd9323e,0xbbf6ae46,0xb61f3b64,0x34a5bba8,0xb23e3bd9,0x2e46bbf6,
0x39a8b9a8,0xb8723aa7,0x361fbb64,0xb23e3bd9,0x39a839a8,0xbaa7b872,0x3b64361f,0xbbd9b23e,0xb61fbb64,0x39133a2f,0xbaa7b872,0x3ba834a5,0x3b64b61f,0xba2f3913,0x3872baa7,0xb4a53ba8,
0xbc008000,0x3b64b61f,0xb9a839a8,0x361fbb64,0xbc00,0x361f3b64,0xb9a8b9a8,0x3b64361f,0xb61f3b64,0xae46bbf6,0x38723aa7,0xbb0eb78b,0xbb64b61f,0x3bf6ae46,0xbaa73872,0x378bbb0e,
0x39a839a8,0xbbd9b23e,0x3b64b61f,0xb8723aa7,0xb9a839a8,0x323ebbd9,0x361f3b64,0xbaa7b872,0x3b64b61f,0xb78b3b0e,0xb23ebbd9,0x3a2f3913,0x361f3b64,0xbb0eb78b,0x3bd9b23e,0xb9133a2f,
0xbc00,0x39a839a8,0xbc008000,0x39a8b9a8,0x3c000000,0xb9a839a8,0xbc00,0x39a839a8,0xbb64b61f,0x3b0eb78b,0xb23e3bd9,0xb913ba2f,0x361fbb64,0x378b3b0e,0xbbd9b23e,0x3a2fb913,
0xb9a839a8,0xb23ebbd9,0x3b64361f,0xbaa73872,0xb9a8b9a8,0x3bd9b23e,0xb61f3b64,0xb872baa7,0x361f3b64,0xbbf6ae46,0x3872baa7,0x378b3b0e,0xbb64361f,0x2e46bbf6,0x3aa73872,0xbb0e378b,
0x3c000000,0xb61f3b64,0xb9a8b9a8,0x3b64b61f,0x80003c00,0xbb64b61f,0x39a8b9a8,0x361f3b64,0x361fbb64,0x3a2f3913,0xbaa73872,0xb4a5bba8,0x3b64361f,0xb9133a2f,0xb872baa7,0x3ba8b4a5,
0xb9a8b9a8,0x3aa7b872,0x361f3b64,0xbbd9323e,0x39a8b9a8,0x38723aa7,0xbb64361f,0xb23ebbd9,0xbb64361f,0xb4a5bba8,0x3bd9b23e,0x2e463bf6,0xb61fbb64,0x3ba8b4a5,0x323e3bd9,0xbbf62e46,
0x3c00,0xbc00,0x3c00,0xbc00,0xbc000000,0x3c000000,0xbc000000,0x3c000000,0x3c000000,0xbbf62e46,0x3bd9b23e,0xbba834a5,0x80003c00,0xae46bbf6,0x323e3bd9,0xb4a5bba8,
0xbc00,0x323e3bd9,0xb61fbb64,0x38723aa7,0x3c000000,0xbbd9323e,0x3b64b61f,0xbaa73872,0xbc008000,0x3ba8b4a5,0xbaa73872,0x3913ba2f,0xbc00,0x34a53ba8,0xb872baa7,0x3a2f3913,
0x3c00,0xb61fbb64,0x39a839a8,0xbb64b61f,0xbc000000,0x3b64b61f,0xb9a839a8,0x361fbb64,0x3c000000,0xbb0e378b,0x3872baa7,0xae463bf6,0x80003c00,0xb78bbb0e,0x3aa73872,0xbbf6ae46,
0xbc00,0x38723aa7,0xbb64b61f,0x3bd9b23e,0x3c000000,0xbaa73872,0x361fbb64,0x323e3bd9,0xbc008000,0x3a2fb913,0xb23e3bd9,0xb78bbb0e,0xbc00,0x39133a2f,0xbbd9b23e,0x3b0eb78b,
0x3c00,0xb9a8b9a8,0x3c000000,0xb9a839a8,0xbc000000,0x39a8b9a8,0x80003c00,0xb9a8b9a8,0x3c000000,0xb9133a2f,0xb23ebbd9,0x3b0e378b,0x80003c00,0xba2fb913,0x3bd9b23e,0xb78b3b0e,
0xbc00,0x3aa73872,0xbb64361f,0x323ebbd9,0x3c000000,0xb8723aa7,0xb61fbb64,0x3bd9323e,0xbc008000,0x378bbb0e,0x38723aa7,0xbbf62e46,0xbc00,0x3b0e378b,0xbaa73872,0xae46bbf6,
0x3c00,0xbb64b61f,0x39a8b9a8,0x361f3b64,0xbc000000,0x361fbb64,0x39a839a8,0xbb64361f,0x3c000000,0xb4a53ba8,0xbaa7b872,0x3a2fb913,0x80003c00,0xbba8b4a5,0x3872baa7,0x39133a2f,
0xbc00,0x3bd9323e,0xb61f3b64,0xbaa7b872,0x3c000000,0xb23e3bd9,0xbb64b61f,0x3872baa7,0xbc008000,0x2e46bbf6,0x3bd9323e,0xb4a53ba8,0xbc00,0x3bf62e46,0xb23e3bd9,0xbba8b4a5,
0x3c00,0xbc00,0x3c00,0xbc00,0xbc000000,0x3c000000,0xbc000000,0x3c000000,0x3b64b61f,0xbb0e378b,0x3aa7b872,0xba2f3913,0x361f3b64,0xb78bbb0e,0x38723aa7,0xb913ba2f,
0xb9a8b9a8,0x3aa73872,0xbb64b61f,0x3bd9323e,0x39a8b9a8,0xb8723aa7,0x361fbb64,0xb23e3bd9,0xb61f3b64,0x2e46bbf6,0x323e3bd9,0xb78bbb0e,0xbb64b61f,0x3bf62e46,0xbbd9323e,0x3b0eb78b,
0x3c000000,0xbb64361f,0x39a8b9a8,0xb61f3b64,0x80003c00,0xb61fbb64,0x39a839a8,0xbb64b61f,0xb61fbb64,0x3a2f3913,0xbbd9b23e,0x3ba8b4a5,0x3b64b61f,0xb9133a2f,0x323ebbd9,0x34a53ba8,
0xb9a839a8,0x323ebbd9,0x361f3b64,0xbaa7b872,0xb9a8b9a8,0x3bd9323e,0xbb64361f,0x3872baa7,0x3b64361f,0xbba834a5,0x3872baa7,0x2e463bf6,0xb61f3b64,0xb4a5bba8,0x3aa73872,0xbbf62e46,
0xbc00,0x39a839a8,0xbc008000,0x39a8b9a8,0x3c000000,0xb9a839a8,0xbc00,0x39a839a8,0xbb64361f,0x34a5bba8,0x38723aa7,0xbbf6ae46,0xb61fbb64,0x3ba834a5,0xbaa73872,0x2e46bbf6,
0x39a839a8,0xbbd9323e,0x361fbb64,0x38723aa7,0xb9a839a8,0xb23ebbd9,0x3b64361f,0xbaa73872,0x361fbb64,0x39133a2f,0xbbd9323e,0x34a5bba8,0x3b64361f,0xba2f3913,0xb23ebbd9,0x3ba834a5,
0xbc008000,0x361fbb64,0x39a839a8,0xbb64361f,0xbc00,0x3b64361f,0xb9a839a8,0xb61fbb64,0x361f3b64,0xbbf62e46,0x323ebbd9,0x3b0e378b,0xbb64361f,0xae46bbf6,0x3bd9323e,0xb78b3b0e,
0x39a8b9a8,0x38723aa7,0xbb64361f,0xb23ebbd9,0x39a839a8,0xbaa73872,0xb61fbb64,0x3bd9b23e,0xbb64b61f,0x378bbb0e,0x3aa73872,0xb9133a2f,0x361fbb64,0x3b0e378b,0xb8723aa7,0xba2fb913,
0x3c00,0xbc00,0x3c00,0xbc00,0xbc000000,0x3c000000,0xbc000000,0x3c000000,0x39a8b9a8,0xb9133a2f,0x3872baa7,0xb78b3b0e,0x39a839a8,0xba2fb913,0x3aa73872,0xbb0eb78b,
0xbc008000,0x3bd9b23e,0xbb64361f,0x3aa7b872,0xbc00,0x323e3bd9,0xb61fbb64,0x38723aa7,0x39a839a8,0xbb0eb78b,0x3bd9323e,0xbbf62e46,0xb9a839a8,0x378bbb0e,0xb23e3bd9,0xae46bbf6,
0xbc00,0x361f3b64,0xb9a8b9a8,0x3b64361f,0x3c000000,0xbb64361f,0x39a8b9a8,0xb61f3b64,0xb9a839a8,0x34a5bba8,0x323e3bd9,0xb913ba2f,0xb9a8b9a8,0x3ba834a5,0xbbd9323e,0x3a2fb913,
0x3c000000,0xbaa73872,0x361fbb64,0x323e3bd9,0x80003c00,0xb872baa7,0x3b64361f,0xbbd9323e,0xb9a8b9a8,0x3bf62e46,0xbaa73872,0x34a5bba8,0x39a8b9a8,0xae463bf6,0xb872baa7,0x3ba834a5,
0x3c00,0xb9a8b9a8,0x3c000000,0xb9a839a8,0xbc000000,0x39a8b9a8,0x80003c00,0xb9a8b9a8,0x39a8b9a8,0x2e463bf6,0xbaa7b872,0x3ba8b4a5,0x39a839a8,0xbbf62e46,0x3872baa7,0x34a53ba8,
0xbc008000,0x3872baa7,0x361f3b64,0xbbd9b23e,0xbc00,0x3aa73872,0xbb64361f,0x323ebbd9,0x39a839a8,0xbba834a5,0x323ebbd9,0x3a2f3913,0xb9a839a8,0xb4a5bba8,0x3bd9323e,0xb9133a2f,
0xbc00,0x3b64361f,0xb9a839a8,0xb61fbb64,0x3c000000,0xb61f3b64,0xb9a8b9a8,0x3b64b61f,0xb9a839a8,0xb78bbb0e,0x3bd9b23e,0xae463bf6,0xb9a8b9a8,0x3b0eb78b,0x323e3bd9,0xbbf6ae46,
0x3c000000,0xb23e3bd9,0xbb64b61f,0x3872baa7,0x80003c00,0xbbd9b23e,0x361fbb64,0x3aa73872,0xb9a8b9a8,0x3a2fb913,0x38723aa7,0xbb0e378b,0x39a8b9a8,0x39133a2f,0xbaa73872,0xb78bbb0e,
0x3c00,0xbc00,0x3c00,0xbc00,0xbc000000,0x3c000000,0xbc000000,0x3c000000,0x361fbb64,0xb4a53ba8,0x323ebbd9,0xae463bf6,0x3b64361f,0xbba8b4a5,0x3bd9323e,0xbbf6ae46,
0xb9a839a8,0x3872baa7,0xb61f3b64,0x323ebbd9,0xb9a8b9a8,0x3aa73872,0xbb64b61f,0x3bd9323e,0x3b64b61f,0xba2f3913,0x3872baa7,0xb4a53ba8,0x361f3b64,0xb913ba2f,0x3aa73872,0xbba8b4a5,
0xbc008000,0x3b64b61f,0xb9a839a8,0x361fbb64,0xbc00,0x361f3b64,0xb9a8b9a8,0x3b64361f,0x3b64361f,0xbbf62e46,0x3aa7b872,0xb78b3b0e,0xb61f3b64,0xae46bbf6,0x38723aa7,0xbb0eb78b,
0xb9a8b9a8,0x3bd9323e,0xbb64361f,0x3872baa7,0x39a8b9a8,0xb23e3bd9,0xb61fbb64,0x3aa73872,0x361f3b64,0xbb0eb78b,0x3bd9b23e,0xb9133a2f,0xbb64361f,0x378bbb0e,0x323e3bd9,0xba2fb913,
0xbc00,0x39a839a8,0xbc008000,0x39a8b9a8,0x3c000000,0xb9a839a8,0xbc00,0x39a839a8,0xb61f3b64,0xb78bbb0e,0x3bd9323e,0xba2f3913,0xbb64b61f,0x3b0eb78b,0xb23e3bd9,0xb913ba2f,
0x39a8b9a8,0x323e3bd9,0xbb64b61f,0x3aa7b872,0x39a839a8,0xbbd9323e,0x361fbb64,0x38723aa7,0xbb64361f,0x2e46bbf6,0x3aa73872,0xbb0e378b,0xb61fbb64,0x3bf62e46,0xb8723aa7,0xb78bbb0e,
0x3c000000,0xb61f3b64,0xb9a8b9a8,0x3b64b61f,0x80003c00,0xbb64b61f,0x39a8b9a8,0x361f3b64,0xbb64b61f,0x3913ba2f,0x38723aa7,0xbba834a5,0x361fbb64,0x3a2f3913,0xbaa73872,0xb4a5bba8,
0x39a839a8,0xbaa73872,0xb61fbb64,0x3bd9b23e,0xb9a839a8,0xb872baa7,0x3b64b61f,0x323e3bd9,0xb61fbb64,0x3ba8b4a5,0x323e3bd9,0xbbf62e46,0x3b64b61f,0x34a53ba8,0xbbd9323e,0xae46bbf6,
0x80003c00,0x8000bc00,0x80003c00,0x8000bc00,0x3c000000,0xbc000000,0x3c000000,0xbc000000,0x8000bc00,0xae463bf6,0x323ebbd9,0xb4a53ba8,0xbc000000,0x3bf62e46,0xbbd9b23e,0x3ba834a5,
0x80003c00,0x323ebbd9,0xb61f3b64,0x3872baa7,0x3c000000,0xbbd9b23e,0x3b64361f,0xbaa7b872,0x8000bc00,0xb4a53ba8,0x3872baa7,0xba2f3913,0xbc000000,0x3ba834a5,0xbaa7b872,0x39133a2f,
0x80003c00,0x361fbb64,0xb9a839a8,0x3b64b61f,0x3c000000,0xbb64b61f,0x39a839a8,0xb61fbb64,0x8000bc00,0xb78b3b0e,0x3aa7b872,0xbbf62e46,0xbc000000,0x3b0e378b,0xb872baa7,0x2e463bf6,
0x80003c00,0x3872baa7,0xbb64361f,0x3bd9323e,0x3c000000,0xbaa7b872,0x361f3b64,0x323ebbd9,0x8000bc00,0xb9133a2f,0x3bd9b23e,0xbb0eb78b,0xbc000000,0x3a2f3913,0xb23ebbd9,0xb78b3b0e,
0x80003c00,0x39a8b9a8,0xbc000000,0x39a839a8,0x3c000000,0xb9a8b9a8,0x3c00,0x39a8b9a8,0x8000bc00,0xba2f3913,0x3bd9323e,0xb78bbb0e,0xbc000000,0x39133a2f,0x323ebbd9,0xbb0e378b,
0x80003c00,0x3aa7b872,0xbb64b61f,0x323e3bd9,0x3c000000,0xb872baa7,0xb61f3b64,0x3bd9b23e,0x8000bc00,0xbb0e378b,0x3aa73872,0x2e46bbf6,0xbc000000,0x378b3b0e,0x3872baa7,0xbbf6ae46,
0x80003c00,0x3b64b61f,0xb9a8b9a8,0xb61f3b64,0x3c000000,0xb61fbb64,0xb9a839a8,0x3b64361f,0x8000bc00,0xbba834a5,0x38723aa7,0x3913ba2f,0xbc000000,0x34a53ba8,0x3aa7b872,0xba2fb913,
0x80003c00,0x3bd9b23e,0xb61fbb64,0xbaa73872,0x3c000000,0xb23ebbd9,0xbb64361f,0x38723aa7,0x8000bc00,0xbbf62e46,0x323e3bd9,0x3ba8b4a5,0xbc000000,0x2e463bf6,0x3bd9b23e,0xb4a5bba8,
0x80003c00,0x8000bc00,0x80003c00,0x8000bc00,0x3c000000,0xbc000000,0x3c000000,0xbc000000,0x361fbb64,0xb78b3b0e,0x3872baa7,0xb9133a2f,0xbb64b61f,0x3b0e378b,0xbaa7b872,0x3a2f3913,
0xb9a839a8,0x3aa7b872,0xbb64361f,0x3bd9b23e,0x39a839a8,0xb872baa7,0x361f3b64,0xb23ebbd9,0x3b64b61f,0xbbf62e46,0x3bd9323e,0xbb0eb78b,0xb61fbb64,0x2e463bf6,0x323ebbd9,0xb78b3b0e,
0xbc000000,0x3b64361f,0xb9a8b9a8,0x361f3b64,0x3c00,0x361fbb64,0xb9a839a8,0x3b64b61f,0x3b64361f,0xb913ba2f,0x323e3bd9,0x34a5bba8,0x361fbb64,0xba2f3913,0x3bd9b23e,0xbba8b4a5,
0xb9a8b9a8,0x323e3bd9,0x361fbb64,0xbaa73872,0xb9a839a8,0x3bd9b23e,0xbb64b61f,0x38723aa7,0x361f3b64,0x34a5bba8,0xbaa73872,0x3bf62e46,0x3b64b61f,0xbba8b4a5,0x38723aa7,0x2e46bbf6,
0x8000bc00,0xb9a839a8,0x3c008000,0xb9a8b9a8,0xbc000000,0x39a839a8,0x8000bc00,0xb9a839a8,0xb61f3b64,0x3ba8b4a5,0xbaa7b872,0x2e463bf6,0x3b64361f,0xb4a5bba8,0xb8723aa7,0x3bf6ae46,
0x39a8b9a8,0xbbd9b23e,0x361f3b64,0x3872baa7,0xb9a8b9a8,0xb23e3bd9,0x3b64b61f,0xbaa7b872,0xbb64361f,0x3a2f3913,0x323ebbd9,0xbba834a5,0x361f3b64,0x3913ba2f,0xbbd9b23e,0x34a53ba8,
0x3c008000,0xb61fbb64,0xb9a839a8,0x3b64361f,0x8000bc00,0xbb64361f,0x39a839a8,0x361fbb64,0xbb64b61f,0xae463bf6,0x3bd9b23e,0xb78bbb0e,0xb61f3b64,0x3bf62e46,0xb23ebbd9,0xbb0e378b,
0x39a839a8,0x3872baa7,0xbb64b61f,0xb23e3bd9,0x39a8b9a8,0xbaa7b872,0xb61f3b64,0x3bd9323e,0xb61fbb64,0xbb0e378b,0x38723aa7,0x3a2fb913,0xbb64361f,0x378b3b0e,0x3aa7b872,0xb913ba2f,
0x80003c00,0x8000bc00,0x80003c00,0x8000bc00,0x3c000000,0xbc000000,0x3c000000,0xbc000000,0x39a8b9a8,0xba2f3913,0x3aa7b872,0xbb0e378b,0xb9a8b9a8,0x39133a2f,0xb872baa7,0x378b3b0e,
0xbc000000,0x3bd9323e,0xbb64b61f,0x3aa73872,0x3c00,0x323ebbd9,0xb61f3b64,0x3872baa7,0x39a839a8,0xb78bbb0e,0x323e3bd9,0x2e46bbf6,0x39a8b9a8,0xbb0e378b,0x3bd9b23e,0xbbf6ae46,
0x8000bc00,0xb61f3b64,0x39a8b9a8,0xbb64361f,0xbc000000,0x3b64361f,0xb9a8b9a8,0x361f3b64,0xb9a839a8,0x3ba8b4a5,0xbbd9b23e,0x3a2f3913,0x39a839a8,0xb4a5bba8,0xb23e3bd9,0x3913ba2f,
0x3c008000,0xbaa7b872,0x361f3b64,0x323ebbd9,0x8000bc00,0xb8723aa7,0x3b64b61f,0xbbd9b23e,0xb9a8b9a8,0x2e463bf6,0x3872baa7,0xbba834a5,0xb9a839a8,0x3bf6ae46,0xbaa7b872,0x34a53ba8,
0x80003c00,0x39a8b9a8,0xbc000000,0x39a839a8,0x3c000000,0xb9a8b9a8,0x3c00,0x39a8b9a8,0x39a8b9a8,0xbbf6ae46,0x38723aa7,0x34a5bba8,0xb9a8b9a8,0xae463bf6,0x3aa7b872,0xbba8b4a5,
0xbc000000,0x38723aa7,0x361fbb64,0xbbd9323e,0x3c00,0x3aa7b872,0xbb64b61f,0x323e3bd9,0x39a839a8,0x34a5bba8,0xbbd9323e,0x39133a2f,0x39a8b9a8,0xbba8b4a5,0x323e3bd9,0x3a2fb913,
0x8000bc00,0xbb64361f,0x39a839a8,0x361fbb64,0xbc000000,0x361f3b64,0x39a8b9a8,0xbb64b61f,0xb9a839a8,0x3b0e378b,0x323ebbd9,0xbbf62e46,0x39a839a8,0x378bbb0e,0xbbd9b23e,0x2e463bf6,
0x3c008000,0xb23ebbd9,0xbb64361f,0x38723aa7,0x8000bc00,0xbbd9323e,0x361f3b64,0x3aa7b872,0xb9a8b9a8,0xb9133a2f,0x3aa73872,0x378bbb0e,0xb9a839a8,0x3a2f3913,0x3872baa7,0xbb0eb78b,
0x80003c00,0x8000bc00,0x80003c00,0x8000bc00,0x3c000000,0xbc000000,0x3c000000,0xbc000000,0x3b64b61f,0xbba834a5,0x3bd9b23e,0xbbf62e46,0xb61fbb64,0x34a53ba8,0xb23ebbd9,0x2e463bf6,
0xb9a8b9a8,0x38723aa7,0xb61fbb64,0x323e3bd9,0xb9a839a8,0x3aa7b872,0xbb64361f,0x3bd9b23e,0xb61f3b64,0x3913ba2f,0xbaa73872,0x3ba8b4a5,0x3b64361f,0xba2fb913,0x38723aa7,0xb4a5bba8,
0x3c008000,0xbb64b61f,0x39a839a8,0xb61fbb64,0x8000bc00,0xb61f3b64,0x39a8b9a8,0xbb64361f,0xb61fbb64,0xae463bf6,0x3872baa7,0xbb0e378b,0xbb64361f,0x3bf62e46,0xbaa7b872,0x378b3b0e,
0xb9a839a8,0x3bd9b23e,0xbb64b61f,0x38723aa7,0x39a839a8,0xb23ebbd9,0xb61f3b64,0x3aa7b872,0x3b64361f,0xb78bbb0e,0xb23e3bd9,0x3a2fb913,0x361fbb64,0xbb0e378b,0x3bd9323e,0xb913ba2f,
0x8000bc00,0xb9a839a8,0x3c008000,0xb9a8b9a8,0xbc000000,0x39a839a8,0x8000bc00,0xb9a839a8,0xbb64361f,0x3b0e378b,0xb23ebbd9,0xb9133a2f,0x361f3b64,0x378bbb0e,0xbbd9323e,0x3a2f3913,
0x39a839a8,0x323ebbd9,0xbb64361f,0x3aa73872,0x39a8b9a8,0xbbd9b23e,0x361f3b64,0x3872baa7,0x361fbb64,0xbbf62e46,0x38723aa7,0x378bbb0e,0xbb64b61f,0x2e463bf6,0x3aa7b872,0xbb0eb78b,
0xbc000000,0x361f3b64,0x39a8b9a8,0xbb64b61f,0x3c00,0x3b64b61f,0xb9a8b9a8,0xb61f3b64,0x361f3b64,0x3a2fb913,0xbaa7b872,0xb4a53ba8,0x3b64b61f,0xb913ba2f,0xb8723aa7,0x3ba834a5,
0x39a8b9a8,0xbaa7b872,0xb61f3b64,0x3bd9323e,0xb9a8b9a8,0xb8723aa7,0x3b64361f,0x323ebbd9,0xbb64b61f,0xb4a53ba8,0x3bd9323e,0x2e46bbf6,0xb61f3b64,0x3ba834a5,0x323ebbd9,0xbbf6ae46,
0x80003c00,0x8000bc00,0x80003c00,0x8000bc00,0x3c000000,0xbc000000,0x3c000000,0xbc000000,0x3c008000,0xbbf6ae46,0x3bd9323e,0xbba8b4a5,0x8000bc00,0xae463bf6,0x323ebbd9,0xb4a53ba8,
0x8000bc00,0xb23e3bd9,0x361fbb64,0xb8723aa7,0xbc000000,0x3bd9323e,0xbb64b61f,0x3aa73872,0xbc000000,0x3ba834a5,0xbaa7b872,0x39133a2f,0x3c00,0x34a5bba8,0xb8723aa7,0x3a2fb913,
0x80003c00,0x361fbb64,0xb9a839a8,0x3b64b61f,0x3c000000,0xbb64b61f,0x39a839a8,0xb61fbb64,0x3c008000,0xbb0eb78b,0x38723aa7,0xae46bbf6,0x8000bc00,0xb78b3b0e,0x3aa7b872,0xbbf62e46,
0x8000bc00,0xb8723aa7,0x3b64b61f,0xbbd9b23e,0xbc000000,0x3aa73872,0xb61fbb64,0xb23e3bd9,0xbc000000,0x3a2f3913,0xb23ebbd9,0xb78b3b0e,0x3c00,0x3913ba2f,0xbbd9323e,0x3b0e378b,
0x80003c00,0x39a8b9a8,0xbc000000,0x39a839a8,0x3c000000,0xb9a8b9a8,0x3c00,0x39a8b9a8,0x3c008000,0xb913ba2f,0xb23e3bd9,0x3b0eb78b,0x8000bc00,0xba2f3913,0x3bd9323e,0xb78bbb0e,
0x8000bc00,0xbaa73872,0x3b64361f,0xb23ebbd9,0xbc000000,0x38723aa7,0x361fbb64,0xbbd9323e,0xbc000000,0x378b3b0e,0x3872baa7,0xbbf6ae46,0x3c00,0x3b0eb78b,0xbaa7b872,0xae463bf6,
0x80003c00,0x3b64b61f,0xb9a8b9a8,0xb61f3b64,0x3c000000,0xb61fbb64,0xb9a839a8,0x3b64361f,0x3c008000,0xb4a5bba8,0xbaa73872,0x3a2f3913,0x8000bc00,0xbba834a5,0x38723aa7,0x3913ba2f,
0x8000bc00,0xbbd9323e,0x361f3b64,0x3aa7b872,0xbc000000,0x323e3bd9,0x3b64b61f,0xb872baa7,0xbc000000,0x2e463bf6,0x3bd9b23e,0xb4a5bba8,0x3c00,0x3bf6ae46,0xb23ebbd9,0xbba834a5,
0x80003c00,0x8000bc00,0x80003c00,0x8000bc00,0x3c000000,0xbc000000,0x3c000000,0xbc000000,0x3b64361f,0xbb0eb78b,0x3aa73872,0xba2fb913,0x361fbb64,0xb78b3b0e,0x3872baa7,0xb9133a2f,
0x39a8b9a8,0xbaa73872,0x3b64b61f,0xbbd9323e,0xb9a8b9a8,0x38723aa7,0xb61fbb64,0x323e3bd9,0xb61fbb64,0x2e463bf6,0x323ebbd9,0xb78b3b0e,0xbb64361f,0x3bf6ae46,0xbbd9b23e,0x3b0e378b,
0xbc000000,0x3b64361f,0xb9a8b9a8,0x361f3b64,0x3c00,0x361fbb64,0xb9a839a8,0x3b64b61f,0xb61f3b64,0x3a2fb913,0xbbd9323e,0x3ba834a5,0x3b64361f,0xb913ba2f,0x323e3bd9,0x34a5bba8,
0x39a839a8,0xb23ebbd9,0xb61f3b64,0x3aa7b872,0x39a8b9a8,0xbbd9323e,0x3b64361f,0xb872baa7,0x3b64b61f,0xbba8b4a5,0x38723aa7,0x2e46bbf6,0xb61fbb64,0xb4a53ba8,0x3aa7b872,0xbbf6ae46,
0x8000bc00,0xb9a839a8,0x3c008000,0xb9a8b9a8,0xbc000000,0x39a839a8,0x8000bc00,0xb9a839a8,0xbb64b61f,0x34a53ba8,0x3872baa7,0xbbf62e46,0xb61f3b64,0x3ba8b4a5,0xbaa7b872,0x2e463bf6,
0xb9a839a8,0x3bd9323e,0xb61fbb64,0xb8723aa7,0x39a839a8,0x323ebbd9,0xbb64361f,0x3aa73872,0x361f3b64,0x3913ba2f,0xbbd9b23e,0x34a53ba8,0x3b64b61f,0xba2fb913,0xb23e3bd9,0x3ba8b4a5,
0x3c008000,0xb61fbb64,0xb9a839a8,0x3b64361f,0x8000bc00,0xbb64361f,0x39a839a8,0x361fbb64,0x361fbb64,0xbbf6ae46,0x323e3bd9,0x3b0eb78b,0xbb64b61f,0xae463bf6,0x3bd9b23e,0xb78bbb0e,
0xb9a8b9a8,0xb8723aa7,0x3b64361f,0x323ebbd9,0xb9a839a8,0x3aa73872,0x361fbb64,0xbbd9b23e,0xbb64361f,0x378b3b0e,0x3aa7b872,0xb913ba2f,0x361f3b64,0x3b0eb78b,0xb872baa7,0xba2f3913,
0x80003c00,0x8000bc00,0x80003c00,0x8000bc00,0x3c000000,0xbc000000,0x3c000000,0xbc000000,0x39a839a8,0xb913ba2f,0x38723aa7,0xb78bbb0e,0x39a8b9a8,0xba2f3913,0x3aa7b872,0xbb0e378b,
0x3c008000,0xbbd9b23e,0x3b64361f,0xbaa7b872,0x8000bc00,0xb23e3bd9,0x361fbb64,0xb8723aa7,0x39a8b9a8,0xbb0e378b,0x3bd9b23e,0xbbf6ae46,0xb9a8b9a8,0x378b3b0e,0xb23ebbd9,0xae463bf6,
0x8000bc00,0xb61f3b64,0x39a8b9a8,0xbb64361f,0xbc000000,0x3b64361f,0xb9a8b9a8,0x361f3b64,0xb9a8b9a8,0x34a53ba8,0x323ebbd9,0xb9133a2f,0xb9a839a8,0x3ba8b4a5,0xbbd9b23e,0x3a2f3913,
0xbc000000,0x3aa73872,0xb61fbb64,0xb23e3bd9,0x3c00,0x3872baa7,0xbb64361f,0x3bd9323e,0xb9a839a8,0x3bf6ae46,0xbaa7b872,0x34a53ba8,0x39a839a8,0xae46bbf6,0xb8723aa7,0x3ba8b4a5,
0x80003c00,0x39a8b9a8,0xbc000000,0x39a839a8,0x3c000000,0xb9a8b9a8,0x3c00,0x39a8b9a8,0x39a839a8,0x2e46bbf6,0xbaa73872,0x3ba834a5,0x39a8b9a8,0xbbf6ae46,0x38723aa7,0x34a5bba8,
0x3c008000,0xb872baa7,0xb61f3b64,0x3bd9b23e,0x8000bc00,0xbaa73872,0x3b64361f,0xb23ebbd9,0x39a8b9a8,0xbba8b4a5,0x323e3bd9,0x3a2fb913,0xb9a8b9a8,0xb4a53ba8,0x3bd9b23e,0xb913ba2f,
0x8000bc00,0xbb64361f,0x39a839a8,0x361fbb64,0xbc000000,0x361f3b64,0x39a8b9a8,0xbb64b61f,0xb9a8b9a8,0xb78b3b0e,0x3bd9323e,0xae46bbf6,0xb9a839a8,0x3b0e378b,0x323ebbd9,0xbbf62e46,
0xbc000000,0x323e3bd9,0x3b64b61f,0xb872baa7,0x3c00,0x3bd9b23e,0xb61fbb64,0xbaa73872,0xb9a839a8,0x3a2f3913,0x3872baa7,0xbb0eb78b,0x39a839a8,0x3913ba2f,0xbaa7b872,0xb78b3b0e,
0x80003c00,0x8000bc00,0x80003c00,0x8000bc00,0x3c000000,0xbc000000,0x3c000000,0xbc000000,0x361f3b64,0xb4a5bba8,0x323e3bd9,0xae46bbf6,0x3b64b61f,0xbba834a5,0x3bd9b23e,0xbbf62e46,
0x39a839a8,0xb872baa7,0x361f3b64,0xb23ebbd9,0x39a8b9a8,0xbaa73872,0x3b64b61f,0xbbd9323e,0x3b64361f,0xba2fb913,0x38723aa7,0xb4a5bba8,0x361fbb64,0xb9133a2f,0x3aa7b872,0xbba834a5,
0x3c008000,0xbb64b61f,0x39a839a8,0xb61fbb64,0x8000bc00,0xb61f3b64,0x39a8b9a8,0xbb64361f,0x3b64b61f,0xbbf6ae46,0x3aa73872,0xb78bbb0e,0xb61fbb64,0xae463bf6,0x3872baa7,0xbb0e378b,
0x39a8b9a8,0xbbd9323e,0x3b64361f,0xb872baa7,0xb9a8b9a8,0x323e3bd9,0x361fbb64,0xbaa73872,0x361fbb64,0xbb0e378b,0x3bd9323e,0xb913ba2f,0xbb64b61f,0x378b3b0e,0x323ebbd9,0xba2f3913,
0x8000bc00,0xb9a839a8,0x3c008000,0xb9a8b9a8,0xbc000000,0x39a839a8,0x8000bc00,0xb9a839a8,0xb61fbb64,0xb78b3b0e,0x3bd9b23e,0xba2fb913,0xbb64361f,0x3b0e378b,0xb23ebbd9,0xb9133a2f,
0xb9a8b9a8,0xb23e3bd9,0x3b64b61f,0xbaa7b872,0xb9a839a8,0x3bd9323e,0xb61fbb64,0xb8723aa7,0xbb64b61f,0x2e463bf6,0x3aa7b872,0xbb0eb78b,0xb61f3b64,0x3bf6ae46,0xb872baa7,0xb78b3b0e,
0xbc000000,0x361f3b64,0x39a8b9a8,0xbb64b61f,0x3c00,0x3b64b61f,0xb9a8b9a8,0xb61f3b64,0xbb64361f,0x39133a2f,0x3872baa7,0xbba8b4a5,0x361f3b64,0x3a2fb913,0xbaa7b872,0xb4a53ba8,
0xb9a839a8,0x3aa73872,0x361fbb64,0xbbd9b23e,0x39a839a8,0x3872baa7,0xbb64b61f,0xb23e3bd9,0xb61f3b64,0x3ba834a5,0x323ebbd9,0xbbf6ae46,0x3b64361f,0x34a5bba8,0xbbd9b23e,0xae463bf6,
0x3c00,0xbc008000,0xbc00,0x3c000000,0xbc000000,0xbc00,0x3c000000,0x80003c00,0x3c00,0xbbf62e46,0xb23ebbd9,0x3ba8b4a5,0xbc000000,0xae46bbf6,0x3bd9b23e,0x34a53ba8,
0x3c00,0xbbd9323e,0xb61fbb64,0x3aa7b872,0xbc000000,0xb23ebbd9,0x3b64b61f,0x38723aa7,0x3c00,0xbba834a5,0xb872baa7,0x3913ba2f,0xbc000000,0xb4a5bba8,0x3aa7b872,0x3a2f3913,
0x3c00,0xbb64361f,0xb9a8b9a8,0x361fbb64,0xbc000000,0xb61fbb64,0x39a8b9a8,0x3b64361f,0x3c00,0xbb0e378b,0xbaa7b872,0x2e46bbf6,0xbc000000,0xb78bbb0e,0x3872baa7,0x3bf62e46,
0x3c00,0xbaa73872,0xbb64b61f,0xb23ebbd9,0xbc000000,0xb872baa7,0x361fbb64,0x3bd9b23e,0x3c00,0xba2f3913,0xbbd9b23e,0xb78bbb0e,0xbc000000,0xb913ba2f,0x323ebbd9,0x3b0eb78b,
0x3c00,0xb9a839a8,0xbc008000,0xb9a8b9a8,0xbc000000,0xb9a8b9a8,0xbc00,0x39a8b9a8,0x3c00,0xb9133a2f,0xbbd9323e,0xbb0eb78b,0xbc000000,0xba2fb913,0xb23ebbd9,0x378bbb0e,
0x3c00,0xb8723aa7,0xbb64361f,0xbbd9b23e,0xbc000000,0xbaa7b872,0xb61fbb64,0x323ebbd9,0x3c00,0xb78b3b0e,0xbaa73872,0xbbf62e46,0xbc000000,0xbb0eb78b,0xb872baa7,0xae46bbf6,
0x3c00,0xb61f3b64,0xb9a839a8,0xbb64361f,0xbc000000,0xbb64b61f,0xb9a8b9a8,0xb61fbb64,0x3c00,0xb4a53ba8,0xb8723aa7,0xba2f3913,0xbc000000,0xbba8b4a5,0xbaa7b872,0xb913ba2f,
0x3c00,0xb23e3bd9,0xb61f3b64,0xb8723aa7,0xbc000000,0xbbd9b23e,0xbb64b61f,0xbaa7b872,0x3c00,0xae463bf6,0xb23e3bd9,0xb4a53ba8,0xbc000000,0xbbf6ae46,0xbbd9b23e,0xbba8b4a5,
0x3c00,0xbc008000,0xbc00,0x3c000000,0xbc000000,0xbc00,0x3c000000,0x80003c00,0x361f3b64,0xbb0e378b,0xb872baa7,0x3a2fb913,0xbb64361f,0xb78bbb0e,0x3aa7b872,0x39133a2f,
0x39a839a8,0xb8723aa7,0xbb64b61f,0x323ebbd9,0xb9a839a8,0xbaa7b872,0x361fbb64,0x3bd9323e,0x3b64361f,0xae463bf6,0xbbd9323e,0xb78bbb0e,0xb61f3b64,0xbbf6ae46,0xb23ebbd9,0x3b0eb78b,
0x3c000000,0x361f3b64,0xb9a839a8,0xbb64b61f,0x80003c00,0xbb64361f,0xb9a8b9a8,0x361fbb64,0x3b64b61f,0x3a2f3913,0xb23e3bd9,0xbba834a5,0x361f3b64,0xb9133a2f,0xbbd9b23e,0xb4a5bba8,
0x39a8b9a8,0x3bd9323e,0x361f3b64,0xb8723aa7,0x39a839a8,0xb23e3bd9,0xbb64361f,0xbaa7b872,0x361fbb64,0x3ba8b4a5,0x3aa73872,0x2e463bf6,0x3b64361f,0x34a53ba8,0xb8723aa7,0xbbf62e46,
0xbc00,0x39a8b9a8,0x3c000000,0x39a839a8,0x3c000000,0x39a839a8,0x80003c00,0xb9a839a8,0xb61fbb64,0x34a5bba8,0x3aa7b872,0x3bf62e46,0x3b64b61f,0x3ba834a5,0x38723aa7,0xae463bf6,
0xb9a8b9a8,0xb23ebbd9,0x361fbb64,0x3aa7b872,0x39a8b9a8,0x3bd9b23e,0x3b64361f,0x38723aa7,0xbb64b61f,0xb913ba2f,0xb23ebbd9,0x34a5bba8,0x361fbb64,0x3a2fb913,0x3bd9b23e,0x3ba834a5,
0xbc008000,0xbb64b61f,0xb9a8b9a8,0xb61fbb64,0xbc00,0x361fbb64,0x39a8b9a8,0x3b64b61f,0xbb64361f,0xbbf62e46,0xbbd9b23e,0xbb0eb78b,0xb61fbb64,0xae46bbf6,0x323ebbd9,0x378bbb0e,
0xb9a839a8,0xbaa73872,0xbb64361f,0xbbd9323e,0xb9a8b9a8,0xb872baa7,0xb61fbb64,0xb23ebbd9,0xb61f3b64,0xb78b3b0e,0xb8723aa7,0xb9133a2f,0xbb64b61f,0xbb0eb78b,0xbaa7b872,0xba2fb913,
0x3c00,0xbc008000,0xbc00,0x3c000000,0xbc000000,0xbc00,0x3c000000,0x80003c00,0x39a839a8,0xb9133a2f,0xbaa7b872,0x378bbb0e,0xb9a839a8,0xba2fb913,0x3872baa7,0x3b0e378b,
0x3c000000,0x323e3bd9,0xbb64361f,0xb872baa7,0x80003c00,0xbbd9323e,0xb61fbb64,0x3aa7b872,0x39a8b9a8,0x3b0e378b,0xb23e3bd9,0xbbf62e46,0x39a839a8,0xb78b3b0e,0xbbd9b23e,0xae46bbf6,
0xbc00,0x3b64b61f,0x39a839a8,0xb61f3b64,0x3c000000,0x361f3b64,0xb9a839a8,0xbb64b61f,0xb9a8b9a8,0x34a5bba8,0x3bd9b23e,0x39133a2f,0x39a8b9a8,0x3ba834a5,0x323e3bd9,0xba2f3913,
0xbc008000,0xb872baa7,0x361fbb64,0x3bd9b23e,0xbc00,0x3aa7b872,0x3b64361f,0x323e3bd9,0xb9a839a8,0xbbf6ae46,0xb872baa7,0x34a5bba8,0xb9a8b9a8,0x2e46bbf6,0x3aa7b872,0x3ba834a5,
0x3c00,0xb9a839a8,0xbc008000,0xb9a8b9a8,0xbc000000,0xb9a8b9a8,0xbc00,0x39a8b9a8,0x39a839a8,0x2e463bf6,0xb8723aa7,0xbba834a5,0xb9a839a8,0xbbf62e46,0xbaa7b872,0xb4a5bba8,
0x3c000000,0x3aa73872,0x361f3b64,0xb23e3bd9,0x80003c00,0xb8723aa7,0xbb64361f,0xbbd9b23e,0x39a8b9a8,0x3ba8b4a5,0x3bd9323e,0x3a2f3913,0x39a839a8,0x34a53ba8,0xb23e3bd9,0xb9133a2f,
0xbc00,0x361fbb64,0x39a8b9a8,0x3b64b61f,0x3c000000,0x3b64361f,0x39a839a8,0x361f3b64,0xb9a8b9a8,0xb78bbb0e,0xb23ebbd9,0x2e46bbf6,0x39a8b9a8,0x3b0eb78b,0x3bd9b23e,0x3bf62e46,
0xbc008000,0xbbd9b23e,0xbb64b61f,0xbaa7b872,0xbc00,0x323ebbd9,0x361fbb64,0x3872baa7,0xb9a839a8,0xba2f3913,0xbaa73872,0xbb0e378b,0xb9a8b9a8,0xb913ba2f,0xb872baa7,0xb78bbb0e,
0x3c00,0xbc008000,0xbc00,0x3c000000,0xbc000000,0xbc00,0x3c000000,0x80003c00,0x3b64361f,0xb4a53ba8,0xbbd9b23e,0x2e46bbf6,0xb61f3b64,0xbba8b4a5,0x323ebbd9,0x3bf62e46,
0x39a8b9a8,0x3aa73872,0xb61f3b64,0xbbd9b23e,0x39a839a8,0xb8723aa7,0xbb64b61f,0x323ebbd9,0xb61fbb64,0x3a2fb913,0x3aa73872,0xb4a53ba8,0x3b64b61f,0x39133a2f,0xb8723aa7,0xbba8b4a5,
0xbc008000,0xb61fbb64,0x39a8b9a8,0x3b64361f,0xbc00,0x3b64b61f,0x39a839a8,0xb61f3b64,0xb61f3b64,0xbbf62e46,0xb872baa7,0x378bbb0e,0xbb64b61f,0xae46bbf6,0x3aa7b872,0x3b0e378b,
0x39a839a8,0xb23e3bd9,0xbb64361f,0xbaa7b872,0xb9a839a8,0xbbd9b23e,0xb61fbb64,0x3872baa7,0x3b64b61f,0x3b0e378b,0x323e3bd9,0xb9133a2f,0x361f3b64,0xb78b3b0e,0xbbd9323e,0xba2fb913,
0xbc00,0x39a8b9a8,0x3c000000,0x39a839a8,0x3c000000,0x39a839a8,0x80003c00,0xb9a839a8,0xbb64b61f,0xb78bbb0e,0x323ebbd9,0x3a2fb913,0x361fbb64,0x3b0eb78b,0x3bd9323e,0x39133a2f,
0xb9a839a8,0xbbd9323e,0xbb64b61f,0xb872baa7,0xb9a8b9a8,0xb23ebbd9,0x361fbb64,0x3aa7b872,0x361f3b64,0xae463bf6,0xb8723aa7,0xbb0e378b,0xbb64361f,0xbbf6ae46,0xbaa7b872,0xb78bbb0e,
0x3c000000,0x3b64361f,0x39a839a8,0x361f3b64,0x80003c00,0xb61f3b64,0xb9a839a8,0xbb64361f,0x361fbb64,0x3913ba2f,0x3aa7b872,0x3ba8b4a5,0x3b64361f,0x3a2f3913,0x38723aa7,0x34a53ba8,
0xb9a8b9a8,0xb872baa7,0xb61fbb64,0xb23ebbd9,0x39a8b9a8,0x3aa7b872,0x3b64b61f,0x3bd9b23e,0xbb64361f,0xbba834a5,0xbbd9323e,0xbbf62e46,0xb61fbb64,0xb4a5bba8,0xb23ebbd9,0xae46bbf6,
0x3c00,0xbc008000,0xbc00,0x3c000000,0xbc000000,0xbc00,0x3c000000,0x80003c00,0x3c000000,0x2e463bf6,0xbbd9323e,0xb4a5bba8,0x80003c00,0xbbf62e46,0xb23ebbd9,0x3ba8b4a5,
0xbc00,0x3bd9b23e,0x361f3b64,0xbaa73872,0x3c000000,0x323e3bd9,0xbb64361f,0xb872baa7,0xbc008000,0xb4a5bba8,0x3aa7b872,0x3a2f3913,0xbc00,0x3ba8b4a5,0x38723aa7,0xb9133a2f,
0x3c00,0xbb64361f,0xb9a8b9a8,0x361fbb64,0xbc000000,0xb61fbb64,0x39a8b9a8,0x3b64361f,0x3c000000,0x378b3b0e,0xb8723aa7,0xbbf6ae46,0x80003c00,0xbb0e378b,0xbaa7b872,0x2e46bbf6,
0xbc00,0x3aa7b872,0x3b64361f,0x323e3bd9,0x3c000000,0x38723aa7,0xb61f3b64,0xbbd9323e,0xbc008000,0xb913ba2f,0x323ebbd9,0x3b0eb78b,0xbc00,0x3a2fb913,0x3bd9323e,0x378b3b0e,
0x3c00,0xb9a839a8,0xbc008000,0xb9a8b9a8,0xbc000000,0xb9a8b9a8,0xbc00,0x39a8b9a8,0x3c000000,0x3a2f3913,0x323e3bd9,0xb78b3b0e,0x80003c00,0xb9133a2f,0xbbd9323e,0xbb0eb78b,
0xbc00,0x3872baa7,0x3b64b61f,0x3bd9323e,0x3c000000,0x3aa73872,0x361f3b64,0xb23e3bd9,0xbc008000,0xbb0eb78b,0xb872baa7,0xae46bbf6,0xbc00,0x378bbb0e,0x3aa7b872,0x3bf6ae46,
0x3c00,0xb61f3b64,0xb9a839a8,0xbb64361f,0xbc000000,0xbb64b61f,0xb9a8b9a8,0xb61fbb64,0x3c000000,0x3ba834a5,0x3aa73872,0x39133a2f,0x80003c00,0xb4a53ba8,0xb8723aa7,0xba2f3913,
0xbc00,0x323ebbd9,0x361fbb64,0x3872baa7,0x3c000000,0x3bd9323e,0x3b64361f,0x3aa73872,0xbc008000,0xbbf6ae46,0xbbd9b23e,0xbba8b4a5,0xbc00,0x2e46bbf6,0x323ebbd9,0x34a5bba8,
0x3c00,0xbc008000,0xbc00,0x3c000000,0xbc000000,0xbc00,0x3c000000,0x80003c00,0x3b64b61f,0x378b3b0e,0xbaa73872,0xb913ba2f,0x361f3b64,0xbb0e378b,0xb872baa7,0x3a2fb913,
0xb9a8b9a8,0x3872baa7,0x3b64361f,0xb23e3bd9,0x39a8b9a8,0x3aa73872,0xb61f3b64,0xbbd9b23e,0xb61f3b64,0xbbf6ae46,0xb23ebbd9,0x3b0eb78b,0xbb64b61f,0x2e46bbf6,0x3bd9b23e,0x378b3b0e,
0x3c000000,0x361f3b64,0xb9a839a8,0xbb64b61f,0x80003c00,0xbb64361f,0xb9a8b9a8,0x361fbb64,0xb61fbb64,0x3913ba2f,0x3bd9323e,0x34a53ba8,0x3b64b61f,0x3a2f3913,0xb23e3bd9,0xbba834a5,
0xb9a839a8,0xbbd9b23e,0xb61fbb64,0x3872baa7,0xb9a8b9a8,0x323ebbd9,0x3b64b61f,0x3aa73872,0x3b64361f,0x34a53ba8,0xb8723aa7,0xbbf62e46,0xb61f3b64,0xbba834a5,0xbaa7b872,0xae46bbf6,
0xbc00,0x39a8b9a8,0x3c000000,0x39a839a8,0x3c000000,0x39a839a8,0x80003c00,0xb9a839a8,0xbb64361f,0xbba8b4a5,0xb872baa7,0x2e46bbf6,0xb61fbb64,0x34a5bba8,0x3aa7b872,0x3bf62e46,
0x39a839a8,0x323e3bd9,0xb61f3b64,0xbaa73872,0xb9a839a8,0xbbd9323e,0xbb64b61f,0xb872baa7,0x361fbb64,0x3a2fb913,0x3bd9b23e,0x3ba834a5,0x3b64361f,0x39133a2f,0x323e3bd9,0xb4a53ba8,
0xbc008000,0xbb64b61f,0xb9a8b9a8,0xb61fbb64,0xbc00,0x361fbb64,0x39a8b9a8,0x3b64b61f,0x361f3b64,0x2e463bf6,0xb23e3bd9,0xb78b3b0e,0xbb64361f,0xbbf62e46,0xbbd9b23e,0xbb0eb78b,
0x39a8b9a8,0x3aa7b872,0x3b64b61f,0x3bd9b23e,0x39a839a8,0x38723aa7,0x361f3b64,0x323e3bd9,0xbb64b61f,0xbb0eb78b,0xbaa7b872,0xba2fb913,0x361fbb64,0x378bbb0e,0x3872baa7,0x3913ba2f,
0x3c00,0xbc008000,0xbc00,0x3c000000,0xbc000000,0xbc00,0x3c000000,0x80003c00,0x39a8b9a8,0x3a2f3913,0xb8723aa7,0xbb0eb78b,0x39a839a8,0xb9133a2f,0xbaa7b872,0x378bbb0e,
0xbc008000,0xb23ebbd9,0x3b64b61f,0x38723aa7,0xbc00,0x3bd9b23e,0x361f3b64,0xbaa73872,0x39a839a8,0xb78b3b0e,0xbbd9b23e,0xae46bbf6,0xb9a839a8,0xbb0eb78b,0x323ebbd9,0x3bf6ae46,
0xbc00,0x3b64b61f,0x39a839a8,0xb61f3b64,0x3c000000,0x361f3b64,0xb9a839a8,0xbb64b61f,0xb9a839a8,0xbba8b4a5,0xb23ebbd9,0x3a2fb913,0xb9a8b9a8,0x34a5bba8,0x3bd9b23e,0x39133a2f,
0x3c000000,0x38723aa7,0xb61f3b64,0xbbd9323e,0x80003c00,0xbaa73872,0xbb64b61f,0xb23ebbd9,0xb9a8b9a8,0x2e46bbf6,0x3aa7b872,0x3ba834a5,0x39a8b9a8,0x3bf62e46,0x38723aa7,0xb4a53ba8,
0x3c00,0xb9a839a8,0xbc008000,0xb9a8b9a8,0xbc000000,0xb9a8b9a8,0xbc00,0x39a8b9a8,0x39a8b9a8,0x3bf6ae46,0x3aa73872,0x34a53ba8,0x39a839a8,0x2e463bf6,0xb8723aa7,0xbba834a5,
0xbc008000,0xbaa7b872,0xb61fbb64,0x323ebbd9,0xbc00,0x3872baa7,0x3b64b61f,0x3bd9323e,0x39a839a8,0x34a53ba8,0xb23e3bd9,0xb9133a2f,0xb9a839a8,0xbba834a5,0xbbd9b23e,0xba2fb913,
0xbc00,0x361fbb64,0x39a8b9a8,0x3b64b61f,0x3c000000,0x3b64361f,0x39a839a8,0x361f3b64,0xb9a839a8,0xbb0e378b,0xbbd9323e,0xbbf6ae46,0xb9a8b9a8,0xb78bbb0e,0xb23ebbd9,0x2e46bbf6,
0x3c000000,0x3bd9323e,0x3b64361f,0x3aa73872,0x80003c00,0xb23e3bd9,0xb61f3b64,0xb8723aa7,0xb9a8b9a8,0xb913ba2f,0xb872baa7,0xb78bbb0e,0x39a8b9a8,0x3a2fb913,0x3aa7b872,0x3b0eb78b,
0x3c00,0xbc008000,0xbc00,0x3c000000,0xbc000000,0xbc00,0x3c000000,0x80003c00,0x361fbb64,0x3ba834a5,0xb23e3bd9,0xbbf6ae46,0x3b64361f,0xb4a53ba8,0xbbd9b23e,0x2e46bbf6,
0xb9a839a8,0xbaa7b872,0x361fbb64,0x3bd9323e,0xb9a8b9a8,0x3872baa7,0x3b64361f,0xb23e3bd9,0x3b64b61f,0x39133a2f,0xb8723aa7,0xbba8b4a5,0x361f3b64,0xba2f3913,0xbaa7b872,0x34a5bba8,
0xbc008000,0xb61fbb64,0x39a8b9a8,0x3b64361f,0xbc00,0x3b64b61f,0x39a839a8,0xb61f3b64,0x3b64361f,0x2e463bf6,0xbaa73872,0xbb0eb78b,0xb61f3b64,0xbbf62e46,0xb872baa7,0x378bbb0e,
0xb9a8b9a8,0x323ebbd9,0x3b64b61f,0x3aa73872,0x39a8b9a8,0x3bd9323e,0x361f3b64,0xb8723aa7,0x361f3b64,0xb78b3b0e,0xbbd9323e,0xba2fb913,0xbb64361f,0xbb0eb78b,0xb23ebbd9,0x3913ba2f,
0xbc00,0x39a8b9a8,0x3c000000,0x39a839a8,0x3c000000,0x39a839a8,0x80003c00,0xb9a839a8,0xb61f3b64,0xbb0e378b,0xbbd9b23e,0xb913ba2f,0xbb64b61f,0xb78bbb0e,0x323ebbd9,0x3a2fb913,
0x39a8b9a8,0x3bd9b23e,0x3b64361f,0x38723aa7,0x39a839a8,0x323e3bd9,0xb61f3b64,0xbaa73872,0xbb64361f,0xbbf6ae46,0xbaa7b872,0xb78bbb0e,0xb61fbb64,0x2e46bbf6,0x3872baa7,0x3b0eb78b,
0x3c000000,0x3b64361f,0x39a839a8,0x361f3b64,0x80003c00,0xb61f3b64,0xb9a839a8,0xbb64361f,0xbb64b61f,0xba2fb913,0xb872baa7,0xb4a5bba8,0x361fbb64,0x3913ba2f,0x3aa7b872,0x3ba8b4a5,
0x39a839a8,0x38723aa7,0x361f3b64,0x323e3bd9,0xb9a839a8,0xbaa73872,0xbb64361f,0xbbd9323e,0xb61fbb64,0xb4a5bba8,0xb23ebbd9,0xae46bbf6,0x3b64b61f,0x3ba8b4a5,0x3bd9b23e,0x3bf6ae46,
0x80003c00,0x3c008000,0x8000bc00,0xbc000000,0x3c000000,0x8000bc00,0xbc000000,0x3c00,0x8000bc00,0xbbf6ae46,0xb23e3bd9,0x3ba834a5,0xbc000000,0xae463bf6,0x3bd9323e,0x34a5bba8,
0x80003c00,0x3bd9323e,0x361fbb64,0xbaa7b872,0x3c000000,0x323ebbd9,0xbb64b61f,0xb8723aa7,0x8000bc00,0xbba8b4a5,0xb8723aa7,0x39133a2f,0xbc000000,0xb4a53ba8,0x3aa73872,0x3a2fb913,
0x80003c00,0x3b64361f,0x39a8b9a8,0xb61fbb64,0x3c000000,0x361fbb64,0xb9a8b9a8,0xbb64361f,0x8000bc00,0xbb0eb78b,0xbaa73872,0x2e463bf6,0xbc000000,0xb78b3b0e,0x38723aa7,0x3bf6ae46,
0x80003c00,0x3aa73872,0x3b64b61f,0x323ebbd9,0x3c000000,0x3872baa7,0xb61fbb64,0xbbd9b23e,0x8000bc00,0xba2fb913,0xbbd9323e,0xb78b3b0e,0xbc000000,0xb9133a2f,0x323e3bd9,0x3b0e378b,
0x80003c00,0x39a839a8,0x3c008000,0x39a8b9a8,0x3c000000,0x39a8b9a8,0x8000bc00,0xb9a8b9a8,0x8000bc00,0xb913ba2f,0xbbd9b23e,0xbb0e378b,0xbc000000,0xba2f3913,0xb23e3bd9,0x378b3b0e,
0x80003c00,0x38723aa7,0x3b64361f,0x3bd9b23e,0x3c000000,0x3aa7b872,0x361fbb64,0xb23ebbd9,0x8000bc00,0xb78bbb0e,0xbaa7b872,0xbbf6ae46,0xbc000000,0xbb0e378b,0xb8723aa7,0xae463bf6,
0x80003c00,0x361f3b64,0x39a839a8,0x3b64361f,0x3c000000,0x3b64b61f,0x39a8b9a8,0x361fbb64,0x8000bc00,0xb4a5bba8,0xb872baa7,0xba2fb913,0xbc000000,0xbba834a5,0xbaa73872,0xb9133a2f,
0x80003c00,0x323e3bd9,0x361f3b64,0x38723aa7,0x3c000000,0x3bd9b23e,0x3b64b61f,0x3aa7b872,0x8000bc00,0xae46bbf6,0xb23ebbd9,0xb4a5bba8,0xbc000000,0xbbf62e46,0xbbd9323e,0xbba834a5,
0x80003c00,0x3c008000,0x8000bc00,0xbc000000,0x3c000000,0x8000bc00,0xbc000000,0x3c00,0x361fbb64,0xbb0eb78b,0xb8723aa7,0x3a2f3913,0xbb64b61f,0xb78b3b0e,0x3aa73872,0x3913ba2f,
0xb9a839a8,0x38723aa7,0x3b64b61f,0xb23ebbd9,0x39a839a8,0x3aa7b872,0xb61fbb64,0xbbd9323e,0x3b64b61f,0xae46bbf6,0xbbd9b23e,0xb78b3b0e,0xb61fbb64,0xbbf62e46,0xb23e3bd9,0x3b0e378b,
0xbc000000,0xb61f3b64,0x39a839a8,0x3b64b61f,0x3c00,0x3b64361f,0x39a8b9a8,0xb61fbb64,0x3b64361f,0x3a2fb913,0xb23ebbd9,0xbba8b4a5,0x361fbb64,0xb913ba2f,0xbbd9323e,0xb4a53ba8,
0xb9a8b9a8,0xbbd9323e,0xb61f3b64,0x38723aa7,0xb9a839a8,0x323e3bd9,0x3b64361f,0x3aa7b872,0x361f3b64,0x3ba834a5,0x3aa7b872,0x2e46bbf6,0x3b64b61f,0x34a5bba8,0xb872baa7,0xbbf6ae46,
0x8000bc00,0xb9a8b9a8,0xbc000000,0xb9a839a8,0xbc000000,0xb9a839a8,0x3c00,0x39a839a8,0xb61f3b64,0x34a53ba8,0x3aa73872,0x3bf6ae46,0x3b64361f,0x3ba8b4a5,0x3872baa7,0xae46bbf6,
0x39a8b9a8,0x323ebbd9,0xb61fbb64,0xbaa7b872,0xb9a8b9a8,0xbbd9b23e,0xbb64361f,0xb8723aa7,0xbb64361f,0xb9133a2f,0xb23e3bd9,0x34a53ba8,0x361f3b64,0x3a2f3913,0x3bd9323e,0x3ba8b4a5,
0x3c008000,0x3b64b61f,0x39a8b9a8,0x361fbb64,0x8000bc00,0xb61fbb64,0xb9a8b9a8,0xbb64b61f,0xbb64b61f,0xbbf6ae46,0xbbd9323e,0xbb0e378b,0xb61f3b64,0xae463bf6,0x323e3bd9,0x378b3b0e,
0x39a839a8,0x3aa73872,0x3b64361f,0x3bd9323e,0x39a8b9a8,0x3872baa7,0x361fbb64,0x323ebbd9,0xb61fbb64,0xb78bbb0e,0xb872baa7,0xb913ba2f,0xbb64361f,0xbb0e378b,0xbaa73872,0xba2f3913,
0x80003c00,0x3c008000,0x8000bc00,0xbc000000,0x3c000000,0x8000bc00,0xbc000000,0x3c00,0x39a8b9a8,0xb913ba2f,0xbaa73872,0x378b3b0e,0xb9a8b9a8,0xba2f3913,0x38723aa7,0x3b0eb78b,
0xbc000000,0xb23e3bd9,0x3b64361f,0x3872baa7,0x3c00,0x3bd9323e,0x361fbb64,0xbaa7b872,0x39a839a8,0x3b0eb78b,0xb23ebbd9,0xbbf6ae46,0x39a8b9a8,0xb78bbb0e,0xbbd9323e,0xae463bf6,
0x8000bc00,0xbb64b61f,0xb9a839a8,0x361f3b64,0xbc000000,0xb61f3b64,0x39a839a8,0x3b64b61f,0xb9a839a8,0x34a53ba8,0x3bd9323e,0x3913ba2f,0x39a839a8,0x3ba8b4a5,0x323ebbd9,0xba2fb913,
0x3c008000,0x3872baa7,0xb61fbb64,0xbbd9b23e,0x8000bc00,0xbaa7b872,0xbb64361f,0xb23e3bd9,0xb9a8b9a8,0xbbf62e46,0xb8723aa7,0x34a53ba8,0xb9a839a8,0x2e463bf6,0x3aa73872,0x3ba8b4a5,
0x80003c00,0x39a839a8,0x3c008000,0x39a8b9a8,0x3c000000,0x39a8b9a8,0x8000bc00,0xb9a8b9a8,0x39a8b9a8,0x2e46bbf6,0xb872baa7,0xbba8b4a5,0xb9a8b9a8,0xbbf6ae46,0xbaa73872,0xb4a53ba8,
0xbc000000,0xbaa73872,0xb61f3b64,0x323e3bd9,0x3c00,0x38723aa7,0x3b64361f,0x3bd9b23e,0x39a839a8,0x3ba834a5,0x3bd9b23e,0x3a2fb913,0x39a8b9a8,0x34a5bba8,0xb23ebbd9,0xb913ba2f,
0x8000bc00,0xb61fbb64,0xb9a8b9a8,0xbb64b61f,0xbc000000,0xbb64361f,0xb9a839a8,0xb61f3b64,0xb9a839a8,0xb78b3b0e,0xb23e3bd9,0x2e463bf6,0x39a839a8,0x3b0e378b,0x3bd9323e,0x3bf6ae46,
0x3c008000,0x3bd9b23e,0x3b64b61f,0x3aa7b872,0x8000bc00,0xb23ebbd9,0xb61fbb64,0xb872baa7,0xb9a8b9a8,0xba2fb913,0xbaa7b872,0xbb0eb78b,0xb9a839a8,0xb9133a2f,0xb8723aa7,0xb78b3b0e,
0x80003c00,0x3c008000,0x8000bc00,0xbc000000,0x3c000000,0x8000bc00,0xbc000000,0x3c00,0x3b64b61f,0xb4a5bba8,0xbbd9323e,0x2e463bf6,0xb61fbb64,0xbba834a5,0x323e3bd9,0x3bf6ae46,
0xb9a8b9a8,0xbaa73872,0x361f3b64,0x3bd9b23e,0xb9a839a8,0x38723aa7,0x3b64b61f,0xb23ebbd9,0xb61f3b64,0x3a2f3913,0x3aa7b872,0xb4a5bba8,0x3b64361f,0x3913ba2f,0xb872baa7,0xbba834a5,
0x3c008000,0x361fbb64,0xb9a8b9a8,0xbb64361f,0x8000bc00,0xbb64b61f,0xb9a839a8,0x361f3b64,0xb61fbb64,0xbbf6ae46,0xb8723aa7,0x378b3b0e,0xbb64361f,0xae463bf6,0x3aa73872,0x3b0eb78b,
0xb9a839a8,0x323e3bd9,0x3b64361f,0x3aa7b872,0x39a839a8,0x3bd9b23e,0x361fbb64,0xb872baa7,0x3b64361f,0x3b0eb78b,0x323ebbd9,0xb913ba2f,0x361fbb64,0xb78bbb0e,0xbbd9b23e,0xba2f3913,
0x8000bc00,0xb9a8b9a8,0xbc000000,0xb9a839a8,0xbc000000,0xb9a839a8,0x3c00,0x39a839a8,0xbb64361f,0xb78b3b0e,0x323e3bd9,0x3a2f3913,0x361f3b64,0x3b0e378b,0x3bd9b23e,0x3913ba2f,
0x39a839a8,0x3bd9323e,0x3b64b61f,0x3872baa7,0x39a8b9a8,0x323ebbd9,0xb61fbb64,0xbaa7b872,0x361fbb64,0xae46bbf6,0xb872baa7,0xbb0eb78b,0xbb64b61f,0xbbf62e46,0xbaa73872,0xb78b3b0e,
0xbc000000,0xbb64361f,0xb9a839a8,0xb61f3b64,0x3c00,0x361f3b64,0x39a839a8,0x3b64361f,0x361f3b64,0x39133a2f,0x3aa73872,0x3ba834a5,0x3b64b61f,0x3a2fb913,0x3872baa7,0x34a5bba8,
0x39a8b9a8,0x3872baa7,0x361fbb64,0x323ebbd9,0xb9a8b9a8,0xbaa7b872,0xbb64b61f,0xbbd9b23e,0xbb64b61f,0xbba8b4a5,0xbbd9b23e,0xbbf6ae46,0xb61f3b64,0xb4a53ba8,0xb23e3bd9,0xae463bf6,
0x80003c00,0x3c008000,0x8000bc00,0xbc000000,0x3c000000,0x8000bc00,0xbc000000,0x3c00,0x3c008000,0x2e46bbf6,0xbbd9b23e,0xb4a53ba8,0x8000bc00,0xbbf6ae46,0xb23e3bd9,0x3ba834a5,
0x8000bc00,0xbbd9b23e,0xb61f3b64,0x3aa73872,0xbc000000,0xb23e3bd9,0x3b64361f,0x3872baa7,0xbc000000,0xb4a53ba8,0x3aa73872,0x3a2fb913,0x3c00,0x3ba834a5,0x3872baa7,0xb913ba2f,
0x80003c00,0x3b64361f,0x39a8b9a8,0xb61fbb64,0x3c000000,0x361fbb64,0xb9a8b9a8,0xbb64361f,0x3c008000,0x378bbb0e,0xb872baa7,0xbbf62e46,0x8000bc00,0xbb0eb78b,0xbaa73872,0x2e463bf6,
0x8000bc00,0xbaa7b872,0xbb64361f,0xb23e3bd9,0xbc000000,0xb8723aa7,0x361f3b64,0x3bd9323e,0xbc000000,0xb9133a2f,0x323e3bd9,0x3b0e378b,0x3c00,0x3a2f3913,0x3bd9b23e,0x378bbb0e,
0x80003c00,0x39a839a8,0x3c008000,0x39a8b9a8,0x3c000000,0x39a8b9a8,0x8000bc00,0xb9a8b9a8,0x3c008000,0x3a2fb913,0x323ebbd9,0xb78bbb0e,0x8000bc00,0xb913ba2f,0xbbd9b23e,0xbb0e378b,
0x8000bc00,0xb872baa7,0xbb64b61f,0xbbd9323e,0xbc000000,0xbaa73872,0xb61f3b64,0x323e3bd9,0xbc000000,0xbb0e378b,0xb8723aa7,0xae463bf6,0x3c00,0x378b3b0e,0x3aa73872,0x3bf62e46,
0x80003c00,0x361f3b64,0x39a839a8,0x3b64361f,0x3c000000,0x3b64b61f,0x39a8b9a8,0x361fbb64,0x3c008000,0x3ba8b4a5,0x3aa7b872,0x3913ba2f,0x8000bc00,0xb4a5bba8,0xb872baa7,0xba2fb913,
0x8000bc00,0xb23ebbd9,0xb61fbb64,0xb872baa7,0xbc000000,0xbbd9323e,0xbb64361f,0xbaa73872,0xbc000000,0xbbf62e46,0xbbd9323e,0xbba834a5,0x3c00,0x2e463bf6,0x323e3bd9,0x34a53ba8,
0x80003c00,0x3c008000,0x8000bc00,0xbc000000,0x3c000000,0x8000bc00,0xbc000000,0x3c00,0x3b64361f,0x378bbb0e,0xbaa7b872,0xb9133a2f,0x361fbb64,0xbb0eb78b,0xb8723aa7,0x3a2f3913,
0x39a8b9a8,0xb872baa7,0xbb64361f,0x323e3bd9,0xb9a8b9a8,0xbaa73872,0x361f3b64,0x3bd9b23e,0xb61fbb64,0xbbf62e46,0xb23e3bd9,0x3b0e378b,0xbb64361f,0x2e463bf6,0x3bd9323e,0x378bbb0e,
0xbc000000,0xb61f3b64,0x39a839a8,0x3b64b61f,0x3c00,0x3b64361f,0x39a8b9a8,0xb61fbb64,0xb61f3b64,0x39133a2f,0x3bd9b23e,0x34a5bba8,0x3b64361f,0x3a2fb913,0xb23ebbd9,0xbba8b4a5,
0x39a839a8,0x3bd9b23e,0x361fbb64,0xb872baa7,0x39a8b9a8,0xb23ebbd9,0xbb64b61f,0xbaa73872,0x3b64b61f,0x34a5bba8,0xb872baa7,0xbbf6ae46,0xb61fbb64,0xbba8b4a5,0xbaa73872,0xae463bf6,
0x8000bc00,0xb9a8b9a8,0xbc000000,0xb9a839a8,0xbc000000,0xb9a839a8,0x3c00,0x39a839a8,0xbb64b61f,0xbba834a5,0xb8723aa7,0x2e463bf6,0xb61f3b64,0x34a53ba8,0x3aa73872,0x3bf6ae46,
0xb9a839a8,0xb23e3bd9,0x361f3b64,0x3aa73872,0x39a839a8,0x3bd9323e,0x3b64b61f,0x3872baa7,0x361f3b64,0x3a2f3913,0x3bd9323e,0x3ba8b4a5,0x3b64b61f,0x3913ba2f,0x323ebbd9,0xb4a5bba8,
0x3c008000,0x3b64b61f,0x39a8b9a8,0x361fbb64,0x8000bc00,0xb61fbb64,0xb9a8b9a8,0xbb64b61f,0x361fbb64,0x2e46bbf6,0xb23ebbd9,0xb78bbb0e,0xbb64b61f,0xbbf6ae46,0xbbd9323e,0xbb0e378b,
0xb9a8b9a8,0xbaa7b872,0xbb64b61f,0xbbd9b23e,0xb9a839a8,0xb8723aa7,0xb61f3b64,0xb23e3bd9,0xbb64361f,0xbb0e378b,0xbaa73872,0xba2f3913,0x361f3b64,0x378b3b0e,0x38723aa7,0x39133a2f,
0x80003c00,0x3c008000,0x8000bc00,0xbc000000,0x3c000000,0x8000bc00,0xbc000000,0x3c00,0x39a839a8,0x3a2fb913,0xb872baa7,0xbb0e378b,0x39a8b9a8,0xb913ba2f,0xbaa73872,0x378b3b0e,
0x3c008000,0x323ebbd9,0xbb64b61f,0xb8723aa7,0x8000bc00,0xbbd9b23e,0xb61f3b64,0x3aa73872,0x39a8b9a8,0xb78bbb0e,0xbbd9323e,0xae463bf6,0xb9a8b9a8,0xbb0e378b,0x323e3bd9,0x3bf62e46,
0x8000bc00,0xbb64b61f,0xb9a839a8,0x361f3b64,0xbc000000,0xb61f3b64,0x39a839a8,0x3b64b61f,0xb9a8b9a8,0xbba834a5,0xb23e3bd9,0x3a2f3913,0xb9a839a8,0x34a53ba8,0x3bd9323e,0x3913ba2f,
0xbc000000,0xb8723aa7,0x361f3b64,0x3bd9323e,0x3c00,0x3aa73872,0x3b64b61f,0x323ebbd9,0xb9a839a8,0x2e463bf6,0x3aa73872,0x3ba8b4a5,0x39a839a8,0x3bf6ae46,0x3872baa7,0xb4a5bba8,
0x80003c00,0x39a839a8,0x3c008000,0x39a8b9a8,0x3c000000,0x39a8b9a8,0x8000bc00,0xb9a8b9a8,0x39a839a8,0x3bf62e46,0x3aa7b872,0x34a5bba8,0x39a8b9a8,0x2e46bbf6,0xb872baa7,0xbba8b4a5,
0x3c008000,0x3aa7b872,0x361fbb64,0xb23ebbd9,0x8000bc00,0xb872baa7,0xbb64b61f,0xbbd9323e,0x39a8b9a8,0x34a5bba8,0xb23ebbd9,0xb913ba2f,0xb9a8b9a8,0xbba8b4a5,0xbbd9323e,0xba2f3913,
0x8000bc00,0xb61fbb64,0xb9a8b9a8,0xbb64b61f,0xbc000000,0xbb64361f,0xb9a839a8,0xb61f3b64,0xb9a8b9a8,0xbb0eb78b,0xbbd9b23e,0xbbf62e46,0xb9a839a8,0xb78b3b0e,0xb23e3bd9,0x2e463bf6,
0xbc000000,0xbbd9323e,0xbb64361f,0xbaa73872,0x3c00,0x323e3bd9,0x361f3b64,0x38723aa7,0xb9a839a8,0xb9133a2f,0xb8723aa7,0xb78b3b0e,0x39a839a8,0x3a2f3913,0x3aa73872,0x3b0e378b,
0x80003c00,0x3c008000,0x8000bc00,0xbc000000,0x3c000000,0x8000bc00,0xbc000000,0x3c00,0x361f3b64,0x3ba8b4a5,0xb23ebbd9,0xbbf62e46,0x3b64b61f,0xb4a5bba8,0xbbd9323e,0x2e463bf6,
0x39a839a8,0x3aa7b872,0xb61fbb64,0xbbd9323e,0x39a8b9a8,0xb872baa7,0xbb64361f,0x323e3bd9,0x3b64361f,0x3913ba2f,0xb872baa7,0xbba834a5,0x361fbb64,0xba2fb913,0xbaa73872,0x34a53ba8,
0x3c008000,0x361fbb64,0xb9a8b9a8,0xbb64361f,0x8000bc00,0xbb64b61f,0xb9a839a8,0x361f3b64,0x3b64b61f,0x2e46bbf6,0xbaa7b872,0xbb0e378b,0xb61fbb64,0xbbf6ae46,0xb8723aa7,0x378b3b0e,
0x39a8b9a8,0xb23ebbd9,0xbb64b61f,0xbaa73872,0xb9a8b9a8,0xbbd9323e,0xb61f3b64,0x38723aa7,0x361fbb64,0xb78bbb0e,0xbbd9b23e,0xba2f3913,0xbb64b61f,0xbb0e378b,0xb23e3bd9,0x39133a2f,
0x8000bc00,0xb9a8b9a8,0xbc000000,0xb9a839a8,0xbc000000,0xb9a839a8,0x3c00,0x39a839a8,0xb61fbb64,0xbb0eb78b,0xbbd9323e,0xb9133a2f,0xbb64361f,0xb78b3b0e,0x323e3bd9,0x3a2f3913,
0xb9a8b9a8,0xbbd9b23e,0xbb64361f,0xb8723aa7,0xb9a839a8,0xb23e3bd9,0x361f3b64,0x3aa73872,0xbb64b61f,0xbbf62e46,0xbaa73872,0xb78b3b0e,0xb61f3b64,0x2e463bf6,0x38723aa7,0x3b0e378b,
0xbc000000,0xbb64361f,0xb9a839a8,0xb61f3b64,0x3c00,0x361f3b64,0x39a839a8,0x3b64361f,0xbb64361f,0xba2f3913,0xb8723aa7,0xb4a53ba8,0x361f3b64,0x39133a2f,0x3aa73872,0x3ba834a5,
0xb9a839a8,0xb8723aa7,0xb61f3b64,0xb23e3bd9,0x39a839a8,0x3aa73872,0x3b64361f,0x3bd9323e,0xb61f3b64,0xb4a53ba8,0xb23e3bd9,0xae463bf6,0x3b64361f,0x3ba834a5,0x3bd9323e,0x3bf62e46,
0x3c003c00,0xa5078000,0x3bfe3c00,0xa9068000,0x3bfc3bfe,0xab89a906,0x3bf23bfa,0xaf86ad05,0x3bf63bfa,0xae46ad05,0x3bd93be7,0xb23eb102,0x3bed3bf2,0xb062af86,0x3bb33bc7,0xb458b378,
0x3be03be7,0xb1a0b102,0x3b813b9c,0xb58ab4f2,0x3bd03bd9,0xb2dcb23e,0x3b443b64,0xb6b3b61f,0x3bbe3bc7,0xb40ab378,0x3afb3b21,0xb7d1b744,0x3ba83bb3,0xb4a5b458,0x3aa73ad2,0xb872b82e,
0x3bfc3c00,0xab898000,0x3b8f3b9c,0xb53eb4f2,0x3be03bf2,0xb1a0af86,0x3b733b81,0xb5d5b58a,0x3ba83bc7,0xb4a5b378,0x3b543b64,0xb669b61f,0x3b543b81,0xb669b58a,0x3b333b44,0xb6fcb6b3,
0x3ae73b21,0xb80cb744,0x3b0e3b21,0xb78bb744,0x3a613aa7,0xb8d4b872,0x3ae73afb,0xb80cb7d1,0x39c43a15,0xb98bb932,0x3abd3ad2,0xb850b82e,0x3913396e,0xba2fb9e0,0x3a903aa7,0xb893b872,
0x3a483a79,0xb8f4b8b4,0x385038b4,0xbabdba79,0x39e03a15,0xb96eb932,0x36fc37d1,0xbb33bafb,0x396e39a8,0xb9e0b9a8,0x353e361f,0xbb8fbb64,0x38f43932,0xba48ba15,0x32dc3458,0xbbd0bbb3,
0x387238b4,0xbaa7ba79,0x2e463102,0xbbf6bbe7,0x37d1382e,0xbafbbad2,0xa5072906,0xbc00bbfe,0x36b33744,0xbb44bb21,0xb062ad05,0xbbedbbfa,0x358a361f,0xbb81bb64,0xb40ab23e,0xbbbebbd9,
0x3a613a79,0xb8d4b8b4,0x345834f2,0xbbb3bb9c,0x3a2f3a48,0xb913b8f4,0x323e3378,0xbbd9bbc7,0x39fb3a15,0xb950b932,0x2f863102,0xbbf2bbe7,0x39c439e0,0xb98bb96e,0x29062d05,0xbbfebbfa,
0x398b39a8,0xb9c4b9a8,0xa9060000,0xbbfebc00,0x3950396e,0xb9fbb9e0,0xaf86ad05,0xbbf2bbfa,0x39133932,0xba2fba15,0xb23eb102,0xbbd9bbe7,0x38d438f4,0xba61ba48,0xb458b378,0xbbb3bbc7,
0xb5d5b4f2,0xbb73bb9c,0x389338b4,0xba90ba79,0xb78bb6b3,0xbb0ebb44,0x38503872,0xbabdbaa7,0xb893b82e,0xba90bad2,0x380c382e,0xbae7bad2,0xb950b8f4,0xb9fbba48,0x378b37d1,0xbb0ebafb,
0xb9fbb9a8,0xb950b9a8,0x36fc3744,0xbb33bb21,0xba90ba48,0xb893b8f4,0x366936b3,0xbb54bb44,0xbb0ebad2,0xb78bb82e,0x35d5361f,0xbb73bb64,0xbb73bb44,0xb5d5b6b3,0x353e358a,0xbb8fbb81,
0xb58ab4f2,0xbb81bb9c,0xbbbebb9c,0xb40ab4f2,0xb6b3b61f,0xbb44bb64,0xbbedbbd9,0xb062b23e,0xb7d1b744,0xbafbbb21,0xbc00bbfa,0xa507ad05,0xb872b82e,0xbaa7bad2,0xbbf6bbfe,0x2e462906,
0xb8f4b8b4,0xba48ba79,0xbbd0bbe7,0x32dc3102,0xb96eb932,0xb9e0ba15,0xbb8fbbb3,0x353e3458,0xb9e0b9a8,0xb96eb9a8,0xbb33bb64,0x36fc361f,0xba48ba15,0xb8f4b932,0xbabdbafb,0x385037d1,
0x34a534f2,0xbba8bb9c,0xbaa7ba79,0xb872b8b4,0x340a3458,0xbbbebbb3,0xbafbbad2,0xb7d1b82e,0x32dc3378,0xbbd0bbc7,0xbb44bb21,0xb6b3b744,0x31a0323e,0xbbe0bbd9,0xbb81bb64,0xb58ab61f,
0x30623102,0xbbedbbe7,0xbbb3bb9c,0xb458b4f2,0x2e462f86,0xbbf6bbf2,0xbbd9bbc7,0xb23eb378,0x2b892d05,0xbbfcbbfa,0xbbf2bbe7,0xaf86b102,0x25072906,0xbc00bbfe,0xbbfebbfa,0xa906ad05,
0xba2fba79,0x391338b4,0x0,0x0,0xb98bb9e0,0x39c4396e,0x0,0x0,0xb8d4b932,0x3a613a15,0x0,0x0,0xb80cb872,0x3ae73aa7,0x0,0x0,
0xb669b744,0x3b543b21,0x0,0x0,0xb4a5b58a,0x3ba83b81,0x0,0x0,0xb1a0b378,0x3be03bc7,0x0,0x0,0xab89af86,0x3bfc3bf2,0x0,0x0,
0x2c002c00,0x80002c00,0x80002c00,0x80002c00,0x2c002c00,0x8a482c00,0x8e482c00,0x90b62c00,0x2c002c00,0x8e482c00,0x92482c00,0x94b62c00,0x2c002c00,0x90b62c00,0x94b62c00,0x97112bff,
0x2c002c00,0x92482c00,0x96482bff,0x98b62bff,0x2c002c00,0x93db2c00,0x97da2bff,0x99e32bfe,0x2c002c00,0x94b62c00,0x98b62bff,0x9b112bfd,0x2c002c00,0x957f2c00,0x997f2bfe,0x9c1f2bfc,
0x2c002c00,0x96482bff,0x9a482bfe,0x9cb52bfa,0x2c002c00,0x97112bff,0x9b112bfd,0x9d4c2bf9,0x2c002c00,0x97da2bff,0x9bd92bfc,0x9de22bf7,0x2c002c00,0x98522bff,0x9c512bfb,0x9e782bf6,
0x2c002c00,0x98b62bff,0x9cb52bfa,0x9f0e2bf4,0x2c002c00,0x991b2bfe,0x9d1a2bf9,0x9fa42bf1,0x2c002c00,0x997f2bfe,0x9d7e2bf8,0xa01d2bef,0x2c002c00,0x99e32bfe,0x9de22bf7,0xa0672bed,
0x2c002c00,0x9a482bfe,0x9e462bf6,0xa0b22bea,0x2c002c00,0x9aac2bfd,0x9eaa2bf5,0xa0fd2be7,0x2c002c00,0x9b112bfd,0x9f0e2bf4,0xa1472be4,0x2c002c00,0x9b752bfd,0x9f722bf2,0xa1912be1,
0x2c002c00,0x9bd92bfc,0x9fd62bf1,0xa1db2bdd,0x2c002c00,0x9c1f2bfc,0xa01d2bef,0xa2262bda,0x2c002c00,0x9c512bfb,0xa04e2bed,0xa26f2bd6,0x2c002c00,0x9c832bfb,0xa0802bec,0xa2b92bd2,
0x2c002c00,0x9cb52bfa,0xa0b22bea,0xa3032bce,0x2c002c00,0x9ce72bfa,0xa0e42be8,0xa34c2bca,0x2c002c00,0x9d1a2bf9,0xa1152be6,0xa3962bc6,0x2c002c00,0x9d4c2bf9,0xa1472be4,0xa3df2bc1,
0x2c002c00,0x9d7e2bf8,0xa1792be2,0xa4142bbc,0x2c002c00,0x9db02bf8,0xa1aa2be0,0xa4382bb7,0x2c002c00,0x9de22bf7,0xa1db2bdd,0xa45d2bb2,0x2c002c00,0x9e142bf7,0xa20d2bdb,0xa4812bad,
0x2c002c00,0x9e462bf6,0xa23e2bd9,0xa4a52ba8,0x2c002c00,0x9e782bf6,0xa26f2bd6,0xa4c92ba2,0x2c002c00,0x9eaa2bf5,0xa2a12bd4,0xa4ed2b9d,0x2c002c00,0x9edc2bf4,0xa2d22bd1,0xa5112b97,
0x2c002c00,0x9f0e2bf4,0xa3032bce,0xa5342b91,0x2c002c00,0x9f402bf3,0xa3342bcb,0xa5582b8a,0x2c002c00,0x9f722bf2,0xa3652bc9,0xa57c2b84,0x2c002c00,0x9fa42bf1,0xa3962bc6,0xa59f2b7d,
0x2c002c00,0x9fd62bf1,0xa3c62bc3,0xa5c22b77,0x2c002c00,0xa0042bf0,0xa3f72bc0,0xa5e52b70,0x2c002c00,0xa01d2bef,0xa4142bbc,0xa6082b69,0x2c002c00,0xa0362bee,0xa42c2bb9,0xa62b2b62,
0x2c002c00,0xa04e2bed,0xa4442bb6,0xa64e2b5a,0x2c002c00,0xa0672bed,0xa45d2bb2,0xa6702b53,0x2c002c00,0xa0802bec,0xa4752baf,0xa6932b4b,0x2c002c00,0xa0992beb,0xa48d2bab,0xa6b52b43,
0x2c002c00,0xa0b22bea,0xa4a52ba8,0xa6d72b3b,0x2c002c00,0xa0cb2be9,0xa4bd2ba4,0xa6f92b33,0x2c002c00,0xa0e42be8,0xa4d52ba0,0xa71b2b2b,0x2c002c00,0xa0fd2be7,0xa4ed2b9d,0xa73d2b22,
0x2c002c00,0xa1152be6,0xa5052b99,0xa75e2b1a,0x2c002c00,0xa12e2be5,0xa51d2b95,0xa7802b11,0x2c002c00,0xa1472be4,0xa5342b91,0xa7a12b08,0x2c002c00,0xa1602be3,0xa54c2b8c,0xa7c22aff,
0x2c002c00,0xa1792be2,0xa5642b88,0xa7e32af6,0x2c002c00,0xa1912be1,0xa57c2b84,0xa8022aed,0x2c002c00,0xa1aa2be0,0xa5932b80,0xa8122ae3,0x2c002c00,0xa1c32bdf,0xa5ab2b7b,0xa8222ad9,
0x2c002c00,0xa1db2bdd,0xa5c22b77,0xa8322ad0,0x2c002c00,0xa1f42bdc,0xa5da2b72,0xa8422ac6,0x2c002c00,0xa20d2bdb,0xa5f12b6e,0xa8522abc,0x2c002c00,0xa2262bda,0xa6082b69,0xa8622ab1,
0x2c002c00,0xa23e2bd9,0xa61f2b64,0xa8722aa7,0x2c002c00,0xa2572bd7,0xa6372b5f,0xa8812a9c,0x2c002c00,0xa26f2bd6,0xa64e2b5a,0xa8912a92,0x2c002c00,0xa2882bd5,0xa6652b55,0xa8a02a87,
0x2c002c00,0xa2a12bd4,0xa67c2b50,0xa8b02a7c,0x2c002c00,0xa2b92bd2,0xa6932b4b,0xa8bf2a71,0x2c002c00,0xa2d22bd1,0xa6aa2b46,0xa8ce2a65,0x2c002c00,0xa2ea2bd0,0xa6c12b41,0xa8dd2a5a,
0x2c002c00,0xa3032bce,0xa6d72b3b,0xa8ec2a4f,0x2c002c00,0xa31b2bcd,0xa6ee2b36,0xa8fb2a43,0x2c002c00,0xa3342bcb,0xa7052b30,0xa9092a37,0x2c002c00,0xa34c2bca,0xa71b2b2b,0xa9182a2b,
0x2c002c00,0xa3652bc9,0xa7322b25,0xa9272a1f,0x2c002c00,0xa37d2bc7,0xa7482b20,0xa9352a13,0x2c002c00,0xa3962bc6,0xa75e2b1a,0xa9432a07,0x2c002c00,0xa3ae2bc4,0xa7752b14,0xa95129fa,
0x2c002c00,0xa3c62bc3,0xa78b2b0e,0xa95f29ed,0x2c002c00,0xa3df2bc1,0xa7a12b08,0xa96d29e1,0x2c002c00,0xa3f72bc0,0xa7b72b02,0xa97b29d4,0x2c002c00,0xa4082bbe,0xa7cd2afc,0xa98929c7,
0x2c002c00,0xa4142bbc,0xa7e32af6,0xa99629ba,0x2c002c00,0xa4202bbb,0xa7f92af0,0xa9a429ad,0x2c002c00,0xa42c2bb9,0xa8072ae9,0xa9b1299f,0x2c002c00,0xa4382bb7,0xa8122ae3,0xa9be2992,
0x2c002c00,0xa4442bb6,0xa81d2add,0xa9cb2984,0x2c002c00,0xa4512bb4,0xa8282ad6,0xa9d82976,0x2c002c00,0xa45d2bb2,0xa8322ad0,0xa9e52969,0x2c002c00,0xa4692bb1,0xa83d2ac9,0xa9f2295b,
0x2c002c00,0xa4752baf,0xa8482ac2,0xa9fe294d,0x2c002c00,0xa4812bad,0xa8522abc,0xaa0b293e,0x2c002c00,0xa48d2bab,0xa85d2ab5,0xaa172930,0x2c002c00,0xa4992baa,0xa8672aae,0xaa232922,
0x2c002c00,0xa4a52ba8,0xa8722aa7,0xaa2f2913,0x2c002c00,0xa4b12ba6,0xa87c2aa0,0xaa3b2905,0x2c002c00,0xa4bd2ba4,0xa8872a99,0xaa4728f6,0x2c002c00,0xa4c92ba2,0xa8912a92,0xaa5228e7,
0x2c002c00,0xa4d52ba0,0xa89b2a8a,0xaa5e28d8,0x2c002c00,0xa4e12b9e,0xa8a62a83,0xaa6928c9,0x2c002c00,0xa4ed2b9d,0xa8b02a7c,0xaa7428ba,0x2c002c00,0xa4f92b9b,0xa8ba2a74,0xaa7f28ab,
0x2c002c00,0xa5052b99,0xa8c42a6d,0xaa8a289b,0x2c002c00,0xa5112b97,0xa8ce2a65,0xaa95288c,0x2c002c00,0xa51d2b95,0xa8d82a5e,0xaaa0287c,0x2c002c00,0xa5292b93,0xa8e22a56,0xaaaa286d,
0x2c002c00,0xa5342b91,0xa8ec2a4f,0xaab5285d,0x2c002c00,0xa5402b8f,0xa8f62a47,0xaabf284d,0x2c002c00,0xa54c2b8c,0xa9002a3f,0xaac9283d,0x2c002c00,0xa5582b8a,0xa9092a37,0xaad3282d,
0x2c002c00,0xa5642b88,0xa9132a2f,0xaadd281d,0x2c002c00,0xa5702b86,0xa91d2a27,0xaae6280d,0x2c002c00,0xa57c2b84,0xa9272a1f,0xaaf027f9,0x2c002c00,0xa5872b82,0xa9302a17,0xaaf927d8,
0x2c002c00,0xa5932b80,0xa93a2a0f,0xab0227b7,0x2c002c00,0xa59f2b7d,0xa9432a07,0xab0b2796,0x2c002c00,0xa5ab2b7b,0xa94d29fe,0xab142775,0x2c002c00,0xa5b62b79,0xa95629f6,0xab1d2753,
0x2c002c00,0xa5c22b77,0xa95f29ed,0xab252732,0x2c002c00,0xa5ce2b74,0xa96929e5,0xab2e2710,0x2c002c00,0xa5da2b72,0xa97229dc,0xab3626ee,0x2c002c00,0xa5e52b70,0xa97b29d4,0xab3e26cc,
0x2c002c00,0xa5f12b6e,0xa98429cb,0xab4626aa,0x2c002c00,0xa5fd2b6b,0xa98d29c3,0xab4e2687,0x2c002c00,0xa6082b69,0xa99629ba,0xab552665,0x2c002c00,0xa6142b67,0xa99f29b1,0xab5d2642,
0x80002c00,0x80002c00,0x80002c00,0x80002c00,0x92482c00,0x93db2c00,0x94b62c00,0x957f2c00,0x96482bff,0x97da2bff,0x98b62bff,0x997f2bfe,0x98b62bff,0x99e32bfe,0x9b112bfd,0x9c1f2bfc,
0x9a482bfe,0x9bd92bfc,0x9cb52bfa,0x9d7e2bf8,0x9bd92bfc,0x9ce72bfa,0x9de22bf7,0x9edc2bf4,0x9cb52bfa,0x9de22bf7,0x9f0e2bf4,0xa01d2bef,0x9d7e2bf8,0x9edc2bf4,0xa01d2bef,0xa0cb2be9,
0x9e462bf6,0x9fd62bf1,0xa0b22bea,0xa1792be2,0x9f0e2bf4,0xa0672bed,0xa1472be4,0xa2262bda,0x9fd62bf1,0xa0e42be8,0xa1db2bdd,0xa2d22bd1,0xa04e2bed,0xa1602be3,0xa26f2bd6,0xa37d2bc7,
0xa0b22bea,0xa1db2bdd,0xa3032bce,0xa4142bbc,0xa1152be6,0xa2572bd7,0xa3962bc6,0xa4692bb1,0xa1792be2,0xa2d22bd1,0xa4142bbc,0xa4bd2ba4,0xa1db2bdd,0xa34c2bca,0xa45d2bb2,0xa5112b97,
0xa23e2bd9,0xa3c62bc3,0xa4a52ba8,0xa5642b88,0xa2a12bd4,0xa4202bbb,0xa4ed2b9d,0xa5b62b79,0xa3032bce,0xa45d2bb2,0xa5342b91,0xa6082b69,0xa3652bc9,0xa4992baa,0xa57c2b84,0xa6592b58,
0xa3c62bc3,0xa4d52ba0,0xa5c22b77,0xa6aa2b46,0xa4142bbc,0xa5112b97,0xa6082b69,0xa6f92b33,0xa4442bb6,0xa54c2b8c,0xa64e2b5a,0xa7482b20,0xa4752baf,0xa5872b82,0xa6932b4b,0xa7962b0b,
0xa4a52ba8,0xa5c22b77,0xa6d72b3b,0xa7e32af6,0xa4d52ba0,0xa5fd2b6b,0xa71b2b2b,0xa8172ae0,0xa5052b99,0xa6372b5f,0xa75e2b1a,0xa83d2ac9,0xa5342b91,0xa6702b53,0xa7a12b08,0xa8622ab1,
0xa5642b88,0xa6aa2b46,0xa7e32af6,0xa8872a99,0xa5932b80,0xa6e32b39,0xa8122ae3,0xa8ab2a7f,0xa5c22b77,0xa71b2b2b,0xa8322ad0,0xa8ce2a65,0xa5f12b6e,0xa7532b1d,0xa8522abc,0xa8f12a4b,
0xa61f2b64,0xa78b2b0e,0xa8722aa7,0xa9132a2f,0xa64e2b5a,0xa7c22aff,0xa8912a92,0xa9352a13,0xa67c2b50,0xa7f92af0,0xa8b02a7c,0xa95629f6,0xa6aa2b46,0xa8172ae0,0xa8ce2a65,0xa97629d8,
0xa6d72b3b,0xa8322ad0,0xa8ec2a4f,0xa99629ba,0xa7052b30,0xa84d2abf,0xa9092a37,0xa9b5299b,0xa7322b25,0xa8672aae,0xa9272a1f,0xa9d4297b,0xa75e2b1a,0xa8812a9c,0xa9432a07,0xa9f2295b,
0xa78b2b0e,0xa89b2a8a,0xa95f29ed,0xaa0f293a,0xa7b72b02,0xa8b52a78,0xa97b29d4,0xaa2b2918,0xa7e32af6,0xa8ce2a65,0xa99629ba,0xaa4728f6,0xa8072ae9,0xa8e72a52,0xa9b1299f,0xaa6228d3,
0xa81d2add,0xa9002a3f,0xa9cb2984,0xaa7c28b0,0xa8322ad0,0xa9182a2b,0xa9e52969,0xaa95288c,0xa8482ac2,0xa9302a17,0xa9fe294d,0xaaae2867,0xa85d2ab5,0xa9482a02,0xaa172930,0xaac62842,
0xa8722aa7,0xa95f29ed,0xaa2f2913,0xaadd281d,0xa8872a99,0xa97629d8,0xaa4728f6,0xaaf327ee,0xa89b2a8a,0xa98d29c3,0xaa5e28d8,0xab0827a1,0xa8b02a7c,0xa9a429ad,0xaa7428ba,0xab1d2753,
0xa8c42a6d,0xa9ba2996,0xaa8a289b,0xab302705,0xa8d82a5e,0xa9d02980,0xaaa0287c,0xab4326b5,0xa8ec2a4f,0xa9e52969,0xaab5285d,0xab552665,0xa9002a3f,0xa9fa2951,0xaac9283d,0xab672614,
0xa9132a2f,0xaa0f293a,0xaadd281d,0xab7725c2,0xa9272a1f,0xaa232922,0xaaf027f9,0xab862570,0xa93a2a0f,0xaa372909,0xab0227b7,0xab95251d,0xa94d29fe,0xaa4b28f1,0xab142775,0xaba224c9,
0xa95f29ed,0xaa5e28d8,0xab252732,0xabaf2475,0xa97229dc,0xaa7128bf,0xab3626ee,0xabbb2420,0xa98429cb,0xaa8328a6,0xab4626aa,0xabc62396,0xa99629ba,0xaa95288c,0xab552665,0xabd022ea,
0xa9a829a8,0xaaa72872,0xab64261f,0xabd9223e,0xa9ba2996,0xaab82858,0xab7225da,0xabe12191,0xa9cb2984,0xaac9283d,0xab802593,0xabe820e4,0xa9dc2972,0xaad92822,0xab8c254c,0xabee2036,
0xa9ed295f,0xaae92807,0xab992505,0xabf41f0e,0xa9fe294d,0xaaf927d8,0xaba424bd,0xabf81db0,0xaa0f293a,0xab0827a1,0xabaf2475,0xabfb1c51,0xaa1f2927,0xab17276a,0xabb9242c,0xabfe19e3,
0xaa2f2913,0xab252732,0xabc323c6,0xabff1648,0xaa3f2900,0xab3326f9,0xabcb2334,0xac000a48,0xaa4f28ec,0xab4126c1,0xabd422a1,0xac0094b6,0xaa5e28d8,0xab4e2687,0xabdb220d,0xabfe991b,
0xaa6d28c4,0xab5a264e,0xabe22179,0xabfc9bd9,0xaa7c28b0,0xab672614,0xabe820e4,0xabf99d4c,0xaa8a289b,0xab7225da,0xabed204e,0xabf59eaa,0xaa992887,0xab7d259f,0xabf21f72,0xabf0a004,
0xaaa72872,0xab882564,0xabf61e46,0xabeaa0b2,0xaab5285d,0xab932529,0xabf91d1a,0xabe3a160,0xaac22848,0xab9d24ed,0xabfc1bd9,0xabdba20d,0xaad02832,0xaba624b1,0xabfe197f,0xabd2a2b9,
0xaadd281d,0xabaf2475,0xabff1648,0xabc9a365,0xaae92807,0xabb72438,0xac000e48,0xabbea408,0xaaf627e3,0xabc023f7,0xac009248,0xabb2a45d,0xab0227b7,0xabc7237d,0xabff97da,0xaba6a4b1,
0xab0e278b,0xabce2303,0xabfe9a48,0xab99a505,0xab1a275e,0xabd52288,0xabfb9c51,0xab8aa558,0xab252732,0xabdb220d,0xabf89d7e,0xab7ba5ab,0xab302705,0xabe12191,0xabf59eaa,0xab6ba5fd,
0xab3b26d7,0xabe62115,0xabf19fd6,0xab5aa64e,0xab4626aa,0xabeb2099,0xabeca080,0xab49a69e,0xab50267c,0xabef201d,0xabe6a115,0xab36a6ee,0xab5a264e,0xabf31f40,0xabe0a1aa,0xab22a73d,
0xab64261f,0xabf61e46,0xabd9a23e,0xab0ea78b,0xab6e25f1,0xabf91d4c,0xabd1a2d2,0xaaf9a7d8,0xab7725c2,0xabfb1c51,0xabc9a365,0xaae3a812,0xab802593,0xabfd1aac,0xabc0a3f7,0xaacca838,
0xab882564,0xabff18b6,0xabb6a444,0xaab5a85d,0xab912534,0xac00157f,0xababa48d,0xaa9ca881,0xab992505,0xac000e48,0xaba0a4d5,0xaa83a8a6,0xaba024d5,0xac0090b6,0xab95a51d,0xaa69a8c9,
0xaba824a5,0xabff9648,0xab88a564,0xaa4fa8ec,0xabaf2475,0xabfe991b,0xab7ba5ab,0xaa33a90e,0xabb62444,0xabfd9b11,0xab6ea5f1,0xaa17a930,0xabbc2414,0xabfb9c83,0xab5fa637,0xa9faa951,
0xabc323c6,0xabf89d7e,0xab50a67c,0xa9dca972,0xabc92365,0xabf69e78,0xab41a6c1,0xa9bea992,0xabce2303,0xabf29f72,0xab30a705,0xa99fa9b1,0xabd422a1,0xabeea036,0xab20a748,0xa980a9d0,
0xabd9223e,0xabeaa0b2,0xab0ea78b,0xa95fa9ed,0xabdd21db,0xabe5a12e,0xaafca7cd,0xa93eaa0b,0xabe22179,0xabe0a1aa,0xaae9a807,0xa91daa27,0xabe62115,0xabdaa226,0xaad6a828,0xa8fbaa43,
0xabea20b2,0xabd4a2a1,0xaac2a848,0xa8d8aa5e,0xabed204e,0xabcda31b,0xaaaea867,0xa8b5aa78,0xabf11fd6,0xabc6a396,0xaa99a887,0xa891aa92,0xabf41f0e,0xabbea408,0xaa83a8a6,0xa86daaaa,
0xabf61e46,0xabb6a444,0xaa6da8c4,0xa848aac2,0xabf81d7e,0xabada481,0xaa56a8e2,0xa822aad9,0xabfa1cb5,0xaba4a4bd,0xaa3fa900,0xa7f9aaf0,0xabfc1bd9,0xab9ba4f9,0xaa27a91d,0xa7acab05,
0xabfe1a48,0xab91a534,0xaa0fa93a,0xa75eab1a,0xabff18b6,0xab86a570,0xa9f6a956,0xa710ab2e,0xabff1648,0xab7ba5ab,0xa9dca972,0xa6c1ab41,0xac001248,0xab70a5e5,0xa9c3a98d,0xa670ab53,
0x80002c00,0x80002c00,0x80002c00,0x80002c00,0x96482bff,0x97112bff,0x97da2bff,0x98522bff,0x9a482bfe,0x9b112bfd,0x9bd92bfc,0x9c512bfb,0x9cb52bfa,0x9d4c2bf9,0x9de22bf7,0x9e782bf6,
0x9e462bf6,0x9f0e2bf4,0x9fd62bf1,0xa04e2bed,0x9fd62bf1,0xa0672bed,0xa0e42be8,0xa1602be3,0xa0b22bea,0xa1472be4,0xa1db2bdd,0xa26f2bd6,0xa1792be2,0xa2262bda,0xa2d22bd1,0xa37d2bc7,
0xa23e2bd9,0xa3032bce,0xa3c62bc3,0xa4442bb6,0xa3032bce,0xa3df2bc1,0xa45d2bb2,0xa4c92ba2,0xa3c62bc3,0xa45d2bb2,0xa4d52ba0,0xa54c2b8c,0xa4442bb6,0xa4c92ba2,0xa54c2b8c,0xa5ce2b74,
0xa4a52ba8,0xa5342b91,0xa5c22b77,0xa64e2b5a,0xa5052b99,0xa59f2b7d,0xa6372b5f,0xa6cc2b3e,0xa5642b88,0xa6082b69,0xa6aa2b46,0xa7482b20,0xa5c22b77,0xa6702b53,0xa71b2b2b,0xa7c22aff,
0xa61f2b64,0xa6d72b3b,0xa78b2b0e,0xa81d2add,0xa67c2b50,0xa73d2b22,0xa7f92af0,0xa8582ab8,0xa6d72b3b,0xa7a12b08,0xa8322ad0,0xa8912a92,0xa7322b25,0xa8022aed,0xa8672aae,0xa8c92a69,
0xa78b2b0e,0xa8322ad0,0xa89b2a8a,0xa9002a3f,0xa7e32af6,0xa8622ab1,0xa8ce2a65,0xa9352a13,0xa81d2add,0xa8912a92,0xa9002a3f,0xa96929e5,0xa8482ac2,0xa8bf2a71,0xa9302a17,0xa99b29b5,
0xa8722aa7,0xa8ec2a4f,0xa95f29ed,0xa9cb2984,0xa89b2a8a,0xa9182a2b,0xa98d29c3,0xa9fa2951,0xa8c42a6d,0xa9432a07,0xa9ba2996,0xaa27291d,0xa8ec2a4f,0xa96d29e1,0xa9e52969,0xaa5228e7,
0xa9132a2f,0xa99629ba,0xaa0f293a,0xaa7c28b0,0xa93a2a0f,0xa9be2992,0xaa372909,0xaaa32877,0xa95f29ed,0xa9e52969,0xaa5e28d8,0xaac9283d,0xa98429cb,0xaa0b293e,0xaa8328a6,0xaaed2802,
0xa9a829a8,0xaa2f2913,0xaaa72872,0xab0e278b,0xa9cb2984,0xaa5228e7,0xaac9283d,0xab2e2710,0xa9ed295f,0xaa7428ba,0xaae92807,0xab4b2693,0xaa0f293a,0xaa95288c,0xab0827a1,0xab672614,
0xaa2f2913,0xaab5285d,0xab252732,0xab802593,0xaa4f28ec,0xaad3282d,0xab4126c1,0xab972511,0xaa6d28c4,0xaaf027f9,0xab5a264e,0xabab248d,0xaa8a289b,0xab0b2796,0xab7225da,0xabbe2408,
0xaaa72872,0xab252732,0xab882564,0xabce2303,0xaac22848,0xab3e26cc,0xab9d24ed,0xabdc21f4,0xaadd281d,0xab552665,0xabaf2475,0xabe820e4,0xaaf627e3,0xab6b25fd,0xabc023f7,0xabf11fa4,
0xab0e278b,0xab802593,0xabce2303,0xabf81d7e,0xab252732,0xab932529,0xabdb220d,0xabfd1aac,0xab3b26d7,0xaba424bd,0xabe62115,0xac0014b6,0xab50267c,0xabb42451,0xabef201d,0xac0093db,
0xab64261f,0xabc323c6,0xabf61e46,0xabfe9a48,0xab7725c2,0xabd022ea,0xabfb1c51,0xabf99d4c,0xab882564,0xabdb220d,0xabff18b6,0xabf29f72,0xab992505,0xabe5212e,0xac000e48,0xabe9a0cb,
0xaba824a5,0xabed204e,0xabff9648,0xabdda1db,0xabb62444,0xabf41edc,0xabfd9b11,0xabd0a2ea,0xabc323c6,0xabf91d1a,0xabf89d7e,0xabc0a3f7,0xabce2303,0xabfd1aac,0xabf29f72,0xabada481,
0xabd9223e,0xabff1648,0xabeaa0b2,0xab99a505,0xabe22179,0xac008a48,0xabe0a1aa,0xab82a587,0xabea20b2,0xabff97da,0xabd4a2a1,0xab69a608,0xabf11fd6,0xabfd9b75,0xabc6a396,0xab4ea687,
0xabf61e46,0xabf89d7e,0xabb6a444,0xab30a705,0xabfa1cb5,0xabf39f40,0xaba4a4bd,0xab11a780,0xabfe1a48,0xabeca080,0xab91a534,0xaaf0a7f9,0xabff1648,0xabe3a160,0xab7ba5ab,0xaacca838,
0xac000000,0xabd9a23e,0xab64a61f,0xaaa7a872,0xabff9648,0xabcda31b,0xab4ba693,0xaa7fa8ab,0xabfe9a48,0xabc0a3f7,0xab30a705,0xaa56a8e2,0xabfa9cb5,0xabb1a469,0xab14a775,0xaa2ba918,
0xabf69e46,0xaba0a4d5,0xaaf6a7e3,0xa9fea94d,0xabf19fd6,0xab8fa540,0xaad6a828,0xa9d0a980,0xabeaa0b2,0xab7ba5ab,0xaab5a85d,0xa99fa9b1,0xabe2a179,0xab67a614,0xaa92a891,0xa96da9e1,
0xabd9a23e,0xab50a67c,0xaa6da8c4,0xa93aaa0f,0xabcea303,0xab39a6e3,0xaa47a8f6,0xa905aa3b,0xabc3a3c6,0xab20a748,0xaa1fa927,0xa8ceaa65,0xabb6a444,0xab05a7ac,0xa9f6a956,0xa896aa8e,
0xaba8a4a5,0xaae9a807,0xa9cba984,0xa85daab5,0xab99a505,0xaacca838,0xa99fa9b1,0xa822aad9,0xab88a564,0xaaaea867,0xa972a9dc,0xa7cdaafc,0xab77a5c2,0xaa8ea896,0xa943aa07,0xa753ab1d,
0xab64a61f,0xaa6da8c4,0xa913aa2f,0xa6d7ab3b,0xab50a67c,0xaa4ba8f1,0xa8e2aa56,0xa659ab58,0xab3ba6d7,0xaa27a91d,0xa8b0aa7c,0xa5daab72,0xab25a732,0xaa02a948,0xa87caaa0,0xa558ab8a,
0xab0ea78b,0xa9dca972,0xa848aac2,0xa4d5aba0,0xaaf6a7e3,0xa9b5a99b,0xa812aae3,0xa451abb4,0xaadda81d,0xa98da9c3,0xa7b7ab02,0xa396abc6,0xaac2a848,0xa964a9e9,0xa748ab20,0xa288abd5,
0xaaa7a872,0xa93aaa0f,0xa6d7ab3b,0xa179abe2,0xaa8aa89b,0xa90eaa33,0xa665ab55,0xa067abed,0xaa6da8c4,0xa8e2aa56,0xa5f1ab6e,0x9eaaabf5,0xaa4fa8ec,0xa8b5aa78,0xa57cab84,0x9c83abfb,
0xaa2fa913,0xa887aa99,0xa505ab99,0x98b6abff,0xaa0fa93a,0xa858aab8,0xa48dabab,0x8a48ac00,0xa9eda95f,0xa828aad6,0xa414abbc,0x17daabff,0xa9cba984,0xa7eeaaf3,0xa334abcb,0x1c1fabfc,
0xa9a8a9a8,0xa78bab0e,0xa23eabd9,0x1e46abf6,0xa984a9cb,0xa726ab28,0xa147abe4,0x2036abee,0xa95fa9ed,0xa6c1ab41,0xa04eabed,0x2147abe4,0xa93aaa0f,0xa659ab58,0x9eaaabf5,0x2257abd7,
0xa913aa2f,0xa5f1ab6e,0x9cb5abfa,0x2365abc9,0xa8ecaa4f,0xa587ab82,0x997fabfe,0x2438abb7,0xa8c4aa6d,0xa51dab95,0x9248ac00,0x24bdaba4,0xa89baa8a,0xa4b1aba6,0x14b6ac00,0x2540ab8f,
0xa872aaa7,0xa444abb6,0x1a48abfe,0x25c2ab77,0xa848aac2,0xa3aeabc4,0x1d1aabf9,0x2642ab5d,0xa81daadd,0xa2d2abd1,0x1f0eabf4,0x26c1ab41,0xa7e3aaf6,0xa1f4abdc,0x2080abec,0x273dab22,
0xa78bab0e,0xa115abe6,0x2179abe2,0x27b7ab02,0xa732ab25,0xa036abee,0x226fabd6,0x2817aae0,0xa6d7ab3b,0x9eaaabf5,0x2365abc9,0x2852aabc,0xa67cab50,0x9ce7abfa,0x242cabb9,0x288caa95,
0xa61fab64,0x9a48abfe,0x24a5aba8,0x28c4aa6d,0xa5c2ab77,0x957fac00,0x251dab95,0x28fbaa43,0xa564ab88,0xe48ac00,0x2593ab80,0x2930aa17,0xa505ab99,0x1852abff,0x2608ab69,0x2964a9e9,
0xa4a5aba8,0x1bd9abfc,0x267cab50,0x2996a9ba,0xa444abb6,0x1db0abf8,0x26eeab36,0x29c7a989,0xa3c6abc3,0x1f72abf2,0x275eab1a,0x29f6a956,0xa303abce,0x2099abeb,0x27cdaafc,0x2a23a922,
0xa23eabd9,0x2179abe2,0x281daadd,0x2a4fa8ec,0xa179abe2,0x2257abd7,0x2852aabc,0x2a78a8b5,0xa0b2abea,0x2334abcb,0x2887aa99,0x2aa0a87c,0x9fd6abf1,0x2408abbe,0x28baaa74,0x2ac6a842,
0x9e46abf6,0x2475abaf,0x28ecaa4f,0x2ae9a807,0x9cb5abfa,0x24e1ab9e,0x291daa27,0x2b0ba796,0x9a48abfe,0x254cab8c,0x294da9fe,0x2b2ba71b,0x9648abff,0x25b6ab79,0x297ba9d4,0x2b49a69e,
0x80002c00,0x80002c00,0x80002c00,0x80002c00,0x98b62bff,0x991b2bfe,0x997f2bfe,0x99e32bfe,0x9cb52bfa,0x9d1a2bf9,0x9d7e2bf8,0x9de22bf7,0x9f0e2bf4,0x9fa42bf1,0xa01d2bef,0xa0672bed,
0xa0b22bea,0xa1152be6,0xa1792be2,0xa1db2bdd,0xa1db2bdd,0xa2572bd7,0xa2d22bd1,0xa34c2bca,0xa3032bce,0xa3962bc6,0xa4142bbc,0xa45d2bb2,0xa4142bbc,0xa4692bb1,0xa4bd2ba4,0xa5112b97,
0xa4a52ba8,0xa5052b99,0xa5642b88,0xa5c22b77,0xa5342b91,0xa59f2b7d,0xa6082b69,0xa6702b53,0xa5c22b77,0xa6372b5f,0xa6aa2b46,0xa71b2b2b,0xa64e2b5a,0xa6cc2b3e,0xa7482b20,0xa7c22aff,
0xa6d72b3b,0xa75e2b1a,0xa7e32af6,0xa8322ad0,0xa75e2b1a,0xa7ee2af3,0xa83d2ac9,0xa8812a9c,0xa7e32af6,0xa83d2ac9,0xa8872a99,0xa8ce2a65,0xa8322ad0,0xa8812a9c,0xa8ce2a65,0xa9182a2b,
0xa8722aa7,0xa8c42a6d,0xa9132a2f,0xa95f29ed,0xa8b02a7c,0xa9052a3b,0xa95629f6,0xa9a429ad,0xa8ec2a4f,0xa9432a07,0xa99629ba,0xa9e52969,0xa9272a1f,0xa98029d0,0xa9d4297b,0xaa232922,
0xa95f29ed,0xa9ba2996,0xaa0f293a,0xaa5e28d8,0xa99629ba,0xa9f2295b,0xaa4728f6,0xaa95288c,0xa9cb2984,0xaa27291d,0xaa7c28b0,0xaac9283d,0xa9fe294d,0xaa5a28dd,0xaaae2867,0xaaf927d8,
0xaa2f2913,0xaa8a289b,0xaadd281d,0xab252732,0xaa5e28d8,0xaab82858,0xab0827a1,0xab4e2687,0xaa8a289b,0xaae32812,0xab302705,0xab7225da,0xaab5285d,0xab0b2796,0xab552665,0xab932529,
0xaadd281d,0xab302705,0xab7725c2,0xabaf2475,0xab0227b7,0xab532670,0xab95251d,0xabc7237d,0xab252732,0xab7225da,0xabaf2475,0xabdb220d,0xab4626aa,0xab8f2540,0xabc62396,0xabeb2099,
0xab64261f,0xaba824a5,0xabd9223e,0xabf61e46,0xab802593,0xabbe2408,0xabe820e4,0xabfd1aac,0xab992505,0xabd122d2,0xabf41f0e,0xac000e48,0xabaf2475,0xabe12191,0xabfb1c51,0xabfe991b,
0xabc323c6,0xabed204e,0xabff1648,0xabf89d7e,0xabd422a1,0xabf71e14,0xac0094b6,0xabeea036,0xabe22179,0xabfd1b11,0xabfc9bd9,0xabe0a1aa,0xabed204e,0xac0013db,0xabf59eaa,0xabcda31b,
0xabf61e46,0xabff9648,0xabeaa0b2,0xabb6a444,0xabfc1bd9,0xabfc9c1f,0xabdba20d,0xab9ba4f9,0xabff1648,0xabf59eaa,0xabc9a365,0xab7ba5ab,0xac009248,0xabeba099,0xabb2a45d,0xab58a659,
0xabfe9a48,0xabdda1db,0xab99a505,0xab30a705,0xabf89d7e,0xabcda31b,0xab7ba5ab,0xab05a7ac,0xabf19fd6,0xabb9a42c,0xab5aa64e,0xaad6a828,0xabe6a115,0xaba2a4c9,0xab36a6ee,0xaaa3a877,
0xabd9a23e,0xab88a564,0xab0ea78b,0xaa6da8c4,0xabc9a365,0xab6ba5fd,0xaae3a812,0xaa33a90e,0xabb6a444,0xab4ba693,0xaab5a85d,0xa9f6a956,0xaba0a4d5,0xab28a726,0xaa83a8a6,0xa9b5a99b,
0xab88a564,0xab02a7b7,0xaa4fa8ec,0xa972a9dc,0xab6ea5f1,0xaad9a822,0xaa17a930,0xa92baa1b,0xab50a67c,0xaaaea867,0xa9dca972,0xa8e2aa56,0xab30a705,0xaa7fa8ab,0xa99fa9b1,0xa896aa8e,
0xab0ea78b,0xaa4fa8ec,0xa95fa9ed,0xa848aac2,0xaae9a807,0xaa1ba92b,0xa91daa27,0xa7eeaaf3,0xaac2a848,0xa9e5a969,0xa8d8aa5e,0xa748ab20,0xaa99a887,0xa9ada9a4,0xa891aa92,0xa69eab49,
0xaa6da8c4,0xa972a9dc,0xa848aac2,0xa5f1ab6e,0xaa3fa900,0xa935aa13,0xa7f9aaf0,0xa540ab8f,0xaa0fa93a,0xa8f6aa47,0xa75eab1a,0xa48dabab,0xa9dca972,0xa8b5aa78,0xa6c1ab41,0xa3aeabc4,
0xa9a8a9a8,0xa872aaa7,0xa61fab64,0xa23eabd9,0xa972a9dc,0xa82daad3,0xa57cab84,0xa0cbabe9,0xa93aaa0f,0xa7cdaafc,0xa4d5aba0,0x9eaaabf5,0xa900aa3f,0xa73dab22,0xa42cabb9,0x9b75abfd,
0xa8c4aa6d,0xa6aaab46,0xa303abce,0x9248ac00,0xa887aa99,0xa614ab67,0xa1aaabe0,0x1852abff,0xa848aac2,0xa57cab84,0xa04eabed,0x1d1aabf9,0xa807aae9,0xa4e1ab9e,0x9de2abf7,0x2004abf0,
0xa78bab0e,0xa444abb6,0x9a48abfe,0x2179abe2,0xa705ab30,0xa34cabca,0x8e48ac00,0x22eaabd0,0xa67cab50,0xa20dabdb,0x18b6abff,0x242cabb9,0xa5f1ab6e,0xa0cbabe9,0x1d1aabf9,0x24e1ab9e,
0xa564ab88,0x9f0eabf4,0x1fd6abf1,0x2593ab80,0xa4d5aba0,0x9c83abfb,0x2147abe4,0x2642ab5d,0xa444abb6,0x97daabff,0x22a1abd4,0x26eeab36,0xa365abc9,0x10b6ac00,0x23f7abc0,0x2796ab0b,
0xa23eabd9,0x1a48abfe,0x24a5aba8,0x281daadd,0xa115abe6,0x1db0abf8,0x254cab8c,0x286daaaa,0x9fd6abf1,0x201dabef,0x25f1ab6e,0x28baaa74,0x9d7eabf8,0x2160abe3,0x2693ab4b,0x2905aa3b,
0x9a48abfe,0x22a1abd4,0x2732ab25,0x294da9fe,0x9248ac00,0x23dfabc1,0x27cdaafc,0x2992a9be,0x1648abff,0x248dabab,0x2832aad0,0x29d4a97b,0x1bd9abfc,0x2529ab93,0x287caaa0,0x2a13a935,
0x1e46abf6,0x25c2ab77,0x28c4aa6d,0x2a4fa8ec,0x204eabed,0x2659ab58,0x2909aa37,0x2a87a8a0,0x2179abe2,0x26eeab36,0x294da9fe,0x2abca852,0x22a1abd4,0x2780ab11,0x298da9c3,0x2aeda802,
0x23c6abc3,0x2807aae9,0x29cba984,0x2b1aa75e,0x2475abaf,0x284daabf,0x2a07a943,0x2b43a6b5,0x2505ab99,0x2891aa92,0x2a3fa900,0x2b69a608,0x2593ab80,0x28d3aa62,0x2a74a8ba,0x2b8aa558,
0x261fab64,0x2913aa2f,0x2aa7a872,0x2ba8a4a5,0x26aaab46,0x2951a9fa,0x2ad6a828,0x2bc1a3df,0x2732ab25,0x298da9c3,0x2b02a7b7,0x2bd6a26f,0x27b7ab02,0x29c7a989,0x2b2ba71b,0x2be7a0fd,
0x281daadd,0x29fea94d,0x2b50a67c,0x2bf49f0e,0x285daab5,0x2a33a90e,0x2b72a5da,0x2bfc9c1f,0x289baa8a,0x2a65a8ce,0x2b91a534,0x2c0094b6,0x28d8aa5e,0x2a95a88c,0x2baba48d,0x2bff1711,
0x2913aa2f,0x2ac2a848,0x2bc3a3c6,0x2bfa1cb5,0x294da9fe,0x2aeda802,0x2bd6a26f,0x2bf11fa4,0x2984a9cb,0x2b14a775,0x2be6a115,0x2be42147,0x29baa996,0x2b39a6e3,0x2bf29f72,0x2bd222b9,
0x29eda95f,0x2b5aa64e,0x2bfa9cb5,0x2bbc2414,0x2a1fa927,0x2b79a5b6,0x2bff97da,0x2ba224c9,0x2a4fa8ec,0x2b95a51d,0x2c001248,0x2b84257c,0x2a7ca8b0,0x2bada481,0x2bfd1b11,0x2b62262b,
0x2aa7a872,0x2bc3a3c6,0x2bf61e46,0x2b3b26d7,0x2ad0a832,0x2bd5a288,0x2bec2080,0x2b112780,0x2af6a7e3,0x2be4a147,0x2bdd21db,0x2ae32812,0x2b1aa75e,0x2bf0a004,0x2bcb2334,0x2ab12862,
0x2b3ba6d7,0x2bf89d7e,0x2bb62444,0x2a7c28b0,0x2b5aa64e,0x2bfe99e3,0x2b9d24ed,0x2a4328fb,0x2b77a5c2,0x2c008e48,0x2b802593,0x2a072943,0x2b91a534,0x2bff1852,0x2b5f2637,0x29c72989,
0x2ba8a4a5,0x2bfa1cb5,0x2b3b26d7,0x298429cb,0x2bbca414,0x2bf31f40,0x2b142775,0x293e2a0b,0x2bcea303,0x2be820e4,0x2ae92807,0x28f62a47,0x2bdda1db,0x2bda2226,0x2abc2852,0x28ab2a7f,
0x2beaa0b2,0x2bc92365,0x2a8a289b,0x285d2ab5,0x2bf49f0e,0x2bb42451,0x2a5628e2,0x280d2ae6,0x2bfa9cb5,0x2b9d24ed,0x2a1f2927,0x27752b14,0x2bff98b6,0x2b822587,0x29e52969,0x26cc2b3e,
0x34003400,0x80003400,0x80003400,0x80003400,0x34003400,0xa24833fe,0xa64633f6,0xa8b233ea,0x34003400,0xa64633f6,0xaa3e33d9,0xaca533a8,0x34003400,0xa8b233ea,0xaca533a8,0xaed7333b,
0x34003400,0xaa3e33d9,0xae1f3364,0xb07232a7,0x34003400,0xabc633c3,0xaf8b330e,0xb15f31ed,0x34003400,0xaca533a8,0xb07232a7,0xb22f3113,0x34003400,0xad643388,0xb113322f,0xb2dd301d,
0x80003400,0x80003400,0x80003400,0x80003400,0xaa3e33d9,0xabc633c3,0xaca533a8,0xad643388,0xae1f3364,0xaf8b330e,0xb07232a7,0xb113322f,0xb07232a7,0xb15f31ed,0xb22f3113,0xb2dd301d,
0xb1a831a8,0xb2a73072,0xb3642e1f,0xb3d92a3e,0xb2a73072,0xb3882d64,0xb3f62646,0xb3eaa8b2,0xb3642e1f,0xb3f62646,0xb3d9aa3e,0xb30eaf8b,0xb3d92a3e,0xb3eaa8b2,0xb30eaf8b,0xb15fb1ed,
0x80003400,0x80003400,0x80003400,0x80003400,0xae1f3364,0xaed7333b,0xaf8b330e,0xb01d32dd,0xb1a831a8,0xb22f3113,0xb2a73072,0xb30e2f8b,0xb3642e1f,0xb3c32bc6,0xb3f62646,0xb3fea248,
0xb4000000,0xb3d9aa3e,0xb364ae1f,0xb2a7b072,0xb364ae1f,0xb26db0c4,0xb113b22f,0xaed7b33b,0xb1a8b1a8,0xaf8bb30e,0xaa3eb3d9,0x2646b3f6,0xae1fb364,0xa248b3fe,0x2ca5b3a8,0x30c4b26d,
0x80003400,0x80003400,0x80003400,0x80003400,0xb07232a7,0xb0c4326d,0xb113322f,0xb15f31ed,0xb3642e1f,0xb3a82ca5,0xb3d92a3e,0xb3f62646,0xb3d9aa3e,0xb388ad64,0xb30eaf8b,0xb26db0c4,
0xb1a8b1a8,0xb072b2a7,0xae1fb364,0xaa3eb3d9,0xaa3eb3d9,0x2248b3fe,0x2ca5b3a8,0x301db2dd,0x2e1fb364,0x3113b22f,0x32a7b072,0x33a8aca5,0x32a7b072,0x33c3abc6,0x33f62646,0x333b2ed7,
};

constexpr int TAB_D80 = 0, TAB_D64 = 6400, TAB_R4 = 14592, TAB_TW1 = 14848, TAB_TW2 = 16896;

enum { FL_WC = 0, FL_WD = 1, FL_Z = 2, FL_Y = 3, FL_W = 4, FL_Y2 = 5, FL_T0 = 72, FL_T1 = 73, FL_T2 = 74, FL_HA = 8  , FL_HB = 40   };

constexpr uint32_t RING = 0;
constexpr uint32_t WSTG = 147456;
constexpr uint32_t SIDE = 172032;
constexpr uint32_t MAT = SIDE, VT = SIDE + 25600;
constexpr uint32_t BEXT = 221184;
constexpr uint32_t MISC = 229376;
constexpr uint32_t B_FULL1 = MISC, B_EMPTY1 = MISC + 32, B_FULL2 = MISC + 64, B_EMPTY2 = MISC + 112;
constexpr uint32_t B_P4 = MISC + 160  , B_EPOCH = MISC + 184, B_WROW = MISC + 192, B_ZIN = MISC + 200, B_WDT = MISC + 208, B_XFREE = MISC + 216;
constexpr uint32_t B_XFULL = MISC + 224, B_TG = MISC + 232, B_WRDY = MISC + 240, B_FA = MISC + 248, B_FB = MISC + 256, B_SPARE = MISC + 264, B_D64 = MISC + 272, B_WC = MISC + 280, B_YFREE = MISC + 288, B_SFREE = MISC + 296, B_P4F = MISC + 304, B_MAT = MISC + 312, B_PAR2 = MISC + 320, B_TB = MISC + 328, B_P2D = MISC + 336;
constexpr uint32_t CSRED = MISC + 2048;
constexpr uint32_t EPOCHV = MISC + 384, FEV = MISC + 388, TBV = MISC + 392, TGV = MISC + 396, WMV = MISC + 400;
constexpr uint32_t E1 = SIDE, E2 = SIDE + 16384, ZIN = SIDE + 32768;
constexpr uint32_t SMEM_BYTES = 232448;
#define T_PF1 5000
#define T_PF2 6000
#define T_R0 9000
#define SLP 200
#define T_X 800
#define T_P1 0
#define T_CS 17000
#define T_S1 900
#define T_PA 2500
#define T_PB 3800
#define T_WDS 100
#define T_P2 8600
#define N_P2 7
#define T_RA 5200
#define N_CA 2
#define N_GA 20
#define T_TILEA ((N_GA - N_CA) * 1024 - 1024)
#define SKIP 0
#define T_WCP 3300
#define T_WC 6300
#define T_WD 7300
#define T_TILEB (5 * 1024 + 128)
#define T_G2 2700

struct alignas(64) Params {
  CUtensorMap mx, mw, mwh, mwd, mxf, mout, my, mz, mcs, mcl;
  const __nv_bfloat16 *x, *wr, *wi, *w0, *w1, *wd;
};

__device__ __forceinline__ void mbar_init(uint32_t bar, uint32_t cnt) { asm volatile("mbarrier.init.shared::cta.b64 [%0], %1;" ::"r"(bar), "r"(cnt) : "memory"); }
__device__ __forceinline__ void mbar_arrive(uint32_t bar) { asm volatile("mbarrier.arrive.shared::cta.b64 _, [%0];" ::"r"(bar) : "memory"); }
__device__ __forceinline__ void release(uint32_t bar, int t) { if (t == 0) mbar_arrive(bar); }
__device__ __forceinline__ void release2(uint32_t bar, int t) {
  if (!MC) release(bar, t);
  else if (t < 2) asm volatile("{\n.reg .b32 ra;\nmapa.shared::cluster.u32 ra, %0, %1;\nmbarrier.arrive.shared::cluster.b64 _, [ra];\n}" ::"r"(bar), "r"(t) : "memory");
}
__device__ __forceinline__ void mbar_wait(uint32_t bar, uint32_t parity) {
  asm volatile("{\n.reg .pred p;\n.reg .u32 c;\nmov.u32 c, 0;\n"
               "LW:\nmbarrier.try_wait.parity.shared::cta.b64 p, [%0], %1;\n@p bra LD;\n"
               "add.u32 c, c, 1;\nsetp.lt.u32 p, c, 4000000;\n@p bra LW;\ntrap;\nLD:\n}" ::"r"(bar), "r"(parity) : "memory");
}
__device__ __forceinline__ void bar_sync(int id, int n) { asm volatile("bar.sync %0, %1;" ::"r"(id), "r"(n) : "memory"); }
__device__ __forceinline__ void bar_arrive(int id, int n) { asm volatile("bar.arrive %0, %1;" ::"r"(id), "r"(n) : "memory"); }
#define ELECT "{\n.reg .pred p;\nelect.sync _|p, 0xffffffff;\n@p "
__device__ __forceinline__ void e_expect(uint32_t bar, uint32_t bytes) { asm volatile(ELECT "mbarrier.arrive.expect_tx.shared::cta.b64 _, [%0], %1;\n}" ::"r"(bar), "r"(bytes) : "memory"); }
__device__ __forceinline__ void e_arrive(uint32_t bar) { asm volatile(ELECT "mbarrier.arrive.shared::cta.b64 _, [%0];\n}" ::"r"(bar) : "memory"); }
__device__ __forceinline__ void e_tma2d(uint32_t dst, const CUtensorMap* m, uint32_t bar, int c0, int c1) {
  asm volatile(ELECT "cp.async.bulk.tensor.2d.shared::cluster.global.mbarrier::complete_tx::bytes [%0], [%1, {%3, %4}], [%2];\n}" ::"r"(dst), "l"(m), "r"(bar), "r"(c0), "r"(c1) : "memory");
}
__device__ __forceinline__ void e_tma3d(uint32_t dst, const CUtensorMap* m, uint32_t bar, int c0, int c1) {
  asm volatile(ELECT "cp.async.bulk.tensor.3d.shared::cluster.global.mbarrier::complete_tx::bytes [%0], [%1, {%3, %4, %5}], [%2];\n}" ::"r"(dst), "l"(m), "r"(bar), "r"(c0), "r"(c1), "r"(0) : "memory");
}
__device__ __forceinline__ void e_tma2d_mc(uint32_t dst, const CUtensorMap* m, uint32_t bar, int c0, int c1) {
  asm volatile(ELECT "cp.async.bulk.tensor.2d.shared::cluster.global.mbarrier::complete_tx::bytes.multicast::cluster [%0], [%1, {%3, %4}], [%2], %5;\n}" ::"r"(dst), "l"(m), "r"(bar), "r"(c0), "r"(c1), "h"((uint16_t)3) : "memory");
}
__device__ __forceinline__ void e_tma3d_mc(uint32_t dst, const CUtensorMap* m, uint32_t bar, int c0, int c1) {
  asm volatile(ELECT "cp.async.bulk.tensor.3d.shared::cluster.global.mbarrier::complete_tx::bytes.multicast::cluster [%0], [%1, {%3, %4, %5}], [%2], %6;\n}" ::"r"(dst), "l"(m), "r"(bar), "r"(c0), "r"(c1), "r"(0), "h"((uint16_t)3) : "memory");
}
__device__ __forceinline__ void e_tma5d(uint32_t dst, const CUtensorMap* m, uint32_t bar, int c0, int c2) {
  asm volatile(ELECT "cp.async.bulk.tensor.5d.shared::cluster.global.mbarrier::complete_tx::bytes [%0], [%1, {%3, %5, %4, %5, %5}], [%2];\n}" ::"r"(dst), "l"(m), "r"(bar), "r"(c0), "r"(c2), "r"(0) : "memory");
}
__device__ __forceinline__ void e_bulk(uint32_t dst, const void* src, uint32_t bytes, uint32_t bar) {
  asm volatile(ELECT "cp.async.bulk.shared::cluster.global.mbarrier::complete_tx::bytes [%0], [%1], %2, [%3];\n}" ::"r"(dst), "l"(src), "r"(bytes), "r"(bar) : "memory");
}
__device__ __forceinline__ void e_pf2d(const CUtensorMap* m, int c0, int c1) { asm volatile(ELECT "cp.async.bulk.prefetch.tensor.2d.L2.global [%0, {%1, %2}];\n}" ::"l"(m), "r"(c0), "r"(c1) : "memory"); }
__device__ __forceinline__ void e_pf3d(const CUtensorMap* m, int c0, int c1) { asm volatile(ELECT "cp.async.bulk.prefetch.tensor.3d.L2.global [%0, {%1, %2, %3}];\n}" ::"l"(m), "r"(c0), "r"(c1), "r"(0) : "memory"); }
__device__ __forceinline__ void e_tma2d_st(const CUtensorMap* m, uint32_t src, int c0, int c1) {
  asm volatile(ELECT "cp.async.bulk.tensor.2d.global.shared::cta.bulk_group [%0, {%2, %3}], [%1];\n}" ::"l"(m), "r"(src), "r"(c0), "r"(c1) : "memory");
}
__device__ __forceinline__ void e_tma4d_st(const CUtensorMap* m, uint32_t src, int c1, int c2) {
  asm volatile(ELECT "cp.async.bulk.tensor.4d.global.shared::cta.bulk_group [%0, {%4, %2, %3, %4}], [%1];\n}" ::"l"(m), "r"(src), "r"(c1), "r"(c2), "r"(0) : "memory");
}
__device__ __forceinline__ void e_tma4d_st3(const CUtensorMap* m, uint32_t src, int c3) {
  asm volatile(ELECT "cp.async.bulk.tensor.4d.global.shared::cta.bulk_group [%0, {%3, %3, %3, %2}], [%1];\n}" ::"l"(m), "r"(src), "r"(c3), "r"(0) : "memory");
}
__device__ __forceinline__ void e_bulk_st(void* dst, uint32_t src, uint32_t bytes) {
  asm volatile(ELECT "cp.async.bulk.global.shared::cta.bulk_group [%0], [%1], %2;\n}" ::"l"(dst), "r"(src), "r"(bytes) : "memory");
}
__device__ __forceinline__ void bulk_commit() { asm volatile("cp.async.bulk.commit_group;" ::: "memory"); }
__device__ __forceinline__ void bulk_wait_read() { asm volatile("cp.async.bulk.wait_group.read 0;" ::: "memory"); }
__device__ __forceinline__ void bulk_wait() { asm volatile("cp.async.bulk.wait_group 0;" ::: "memory"); }
__device__ __forceinline__ void prefetch_map(const CUtensorMap* m) { asm volatile("prefetch.tensormap [%0];" ::"l"(m) : "memory"); }
__device__ __forceinline__ void wg_fence() { asm volatile("wgmma.fence.sync.aligned;" ::: "memory"); }
__device__ __forceinline__ void wg_commit() { asm volatile("wgmma.commit_group.sync.aligned;" ::: "memory"); }
template <int N> __device__ __forceinline__ void wg_wait() { asm volatile("wgmma.wait_group.sync.aligned %0;" ::"n"(N) : "memory"); }
__device__ __forceinline__ void fence_async_smem() { asm volatile("fence.proxy.async.shared::cta;" ::: "memory"); }
__device__ __forceinline__ void fence_async_glob() { asm volatile("fence.proxy.async.global;" ::: "memory"); }
__host__ __device__ constexpr uint64_t desc_hi(uint32_t lbo, uint32_t sbo, int swz) { return ((uint64_t)(lbo >> 4) << 16) | ((uint64_t)(sbo >> 4) << 32) | ((uint64_t)swz << 62); }
__device__ __forceinline__ uint64_t desc(uint64_t hi, uint32_t addr) { return hi | (uint64_t)((addr & 0x3FFFF) >> 4); }
__device__ __forceinline__ void fence_gpu() { asm volatile("fence.acq_rel.gpu;" ::: "memory"); }
__device__ __forceinline__ void e_publish(int flag) { asm volatile(ELECT "red.relaxed.gpu.global.add.u32 [%0], 1;\n}" ::"l"(g_flag + flag * 32) : "memory"); }
__device__ __forceinline__ uint32_t readback(const void* p) { uint32_t v; asm volatile("ld.relaxed.gpu.global.u32 %0, [%1];" : "=r"(v) : "l"(p) : "memory"); return v; }
__device__ __forceinline__ void settle(uint32_t v) { asm volatile("{\n.reg .pred p;\nsetp.eq.u32 p, %0, 0;\nvote.sync.all.pred p, p, 0xffffffff;\n}" ::"r"(v) : "memory"); }
__device__ __forceinline__ void poll(int flag, unsigned target) {
  unsigned v; int n = 0;
  do {
    asm volatile("ld.relaxed.gpu.global.u32 %0, [%1];" : "=r"(v) : "l"(g_flag + flag * 32) : "memory");
    if (SLP && n) __nanosleep(SLP);
    if (++n > 3000000) __trap();
  } while ((int)(v - target) < 0);
}
__device__ __forceinline__ void acquire() { asm volatile("fence.acquire.gpu;\nfence.proxy.async.global;" ::: "memory"); }
__device__ __forceinline__ uint2 ld_tag(const uint2* p) { uint64_t v; asm volatile("ld.relaxed.gpu.global.b64 %0, [%1];" : "=l"(v) : "l"(p) : "memory"); return make_uint2((uint32_t)v, (uint32_t)(v >> 32)); }
__device__ __forceinline__ void st_tag(uint2* p, uint32_t x, uint32_t y) { asm volatile("st.relaxed.gpu.global.b64 [%0], %1;" ::"l"(p), "l"(((uint64_t)y << 32) | x) : "memory"); }
__device__ __forceinline__ unsigned clk() { unsigned c; asm volatile("mov.u32 %0, %%clock;" : "=r"(c)); return c; }
__device__ __forceinline__ void post_max(int flag, unsigned ep1, unsigned v) {
  asm volatile("red.relaxed.gpu.global.max.u64 [%0+8], %1;\nred.relaxed.gpu.global.add.u32 [%0], 1;" ::"l"(g_flag + flag * 32), "l"(((uint64_t)ep1 << 32) | v) : "memory");
}
__device__ __forceinline__ unsigned poll_max(int flag, unsigned ep1) {
  uint4 v; int n = 0;
  do {
    asm volatile("ld.relaxed.gpu.global.v4.u32 {%0,%1,%2,%3}, [%4];" : "=r"(v.x), "=r"(v.y), "=r"(v.z), "=r"(v.w) : "l"(g_flag + flag * 32) : "memory");
    if (SLP && n) __nanosleep(SLP);
    if (++n > 3000000) __trap();
  } while ((int)(v.x - ep1 * 128) < 0);
  return v.z;
}
__device__ __forceinline__ void wait_until(unsigned t) {
  int d;
  while ((d = (int)(t - clk())) > 0) __nanosleep(d >> 2);
}
__device__ __forceinline__ float2 cispi(float x) { const float a = x * 3.14159265358979324f; return make_float2(__cosf(a), __sinf(a)); }
__device__ __forceinline__ float tanh_fast(float x) { float y; asm("tanh.approx.f32 %0, %1;" : "=f"(y) : "f"(x)); return y; }
__device__ __forceinline__ uint32_t pack_bf16(float lo, float hi) { uint32_t r; asm("cvt.rn.bf16x2.f32 %0, %1, %2;" : "=r"(r) : "f"(hi), "f"(lo)); return r; }
__device__ __forceinline__ uint32_t pack_f16(float lo, float hi) { uint32_t r; asm("cvt.rn.f16x2.f32 %0, %1, %2;" : "=r"(r) : "f"(hi), "f"(lo)); return r; }
__device__ __forceinline__ float bf_lo(uint32_t v) { return __uint_as_float(v << 16); }
__device__ __forceinline__ float bf_hi(uint32_t v) { return __uint_as_float(v & 0xffff0000u); }
__device__ __forceinline__ float bf_round(float v) { return __bfloat162float(__float2bfloat16_rn(v)); }
__device__ __forceinline__ uint32_t hmul2_bf(uint32_t a, uint32_t b) { uint32_t r; asm("mul.rn.bf16x2 %0, %1, %2;" : "=r"(r) : "r"(a), "r"(b)); return r; }
__device__ __forceinline__ uint32_t hadd2_bf(uint32_t a, uint32_t b) { uint32_t r; asm("add.rn.bf16x2 %0, %1, %2;" : "=r"(r) : "r"(a), "r"(b)); return r; }
__device__ __forceinline__ void sts32(uint32_t a, uint32_t v) { asm volatile("st.shared.b32 [%0], %1;" ::"r"(a), "r"(v) : "memory"); }
__device__ __forceinline__ void sts128(uint32_t a, uint32_t x, uint32_t y, uint32_t z, uint32_t w) { asm volatile("st.shared.v4.b32 [%0], {%1,%2,%3,%4};" ::"r"(a), "r"(x), "r"(y), "r"(z), "r"(w) : "memory"); }
__device__ __forceinline__ uint32_t lds32(uint32_t a) { uint32_t v; asm volatile("ld.shared.b32 %0, [%1];" : "=r"(v) : "r"(a) : "memory"); return v; }
__device__ __forceinline__ uint32_t lds16(uint32_t a) { uint16_t v; asm volatile("ld.shared.u16 %0, [%1];" : "=h"(v) : "r"(a) : "memory"); return v; }
__device__ __forceinline__ float2 lds64f(uint32_t a) { float2 v; asm volatile("ld.shared.v2.f32 {%0,%1}, [%2];" : "=f"(v.x), "=f"(v.y) : "r"(a) : "memory"); return v; }
__device__ __forceinline__ uint4 lds128(uint32_t a) { uint4 v; asm volatile("ld.shared.v4.b32 {%0,%1,%2,%3}, [%4];" : "=r"(v.x), "=r"(v.y), "=r"(v.z), "=r"(v.w) : "r"(a) : "memory"); return v; }
__device__ __forceinline__ void stg128(void* p, uint32_t x, uint32_t y, uint32_t z, uint32_t w) { asm volatile("st.global.v4.b32 [%0], {%1,%2,%3,%4};" ::"l"(p), "r"(x), "r"(y), "r"(z), "r"(w) : "memory"); }
__device__ __forceinline__ void sts64(uint32_t a, uint32_t x, uint32_t y) { asm volatile("st.shared.v2.b32 [%0], {%1,%2};" ::"r"(a), "r"(x), "r"(y) : "memory"); }
__device__ __forceinline__ uint2 lds64(uint32_t a) { uint2 v; asm volatile("ld.shared.v2.b32 {%0,%1}, [%2];" : "=r"(v.x), "=r"(v.y) : "r"(a) : "memory"); return v; }
__device__ __forceinline__ uint4 ldsm4(uint32_t a) { uint4 v; asm volatile("ldmatrix.sync.aligned.m8n8.x4.shared.b16 {%0,%1,%2,%3}, [%4];" : "=r"(v.x), "=r"(v.y), "=r"(v.z), "=r"(v.w) : "r"(a) : "memory"); return v; }
__device__ __forceinline__ uint4 ldsm4t(uint32_t a) { uint4 v; asm volatile("ldmatrix.sync.aligned.m8n8.x4.trans.shared.b16 {%0,%1,%2,%3}, [%4];" : "=r"(v.x), "=r"(v.y), "=r"(v.z), "=r"(v.w) : "r"(a) : "memory"); return v; }
__device__ __forceinline__ void stsm4(uint32_t a, uint32_t x, uint32_t y, uint32_t z, uint32_t w) { asm volatile("stmatrix.sync.aligned.m8n8.x4.shared.b16 [%0], {%1,%2,%3,%4};" ::"r"(a), "r"(x), "r"(y), "r"(z), "r"(w) : "memory"); }
__device__ __forceinline__ void sts16(uint32_t a, uint32_t v) { asm volatile("st.shared.b16 [%0], %1;" ::"r"(a), "h"((uint16_t)v) : "memory"); }
__device__ __forceinline__ uint32_t h2u(__half2 v) { return *(uint32_t*)&v; }
__device__ __forceinline__ __half2 u2h(uint32_t v) { return *(__half2*)&v; }
__device__ __forceinline__ void prefetch_l2(const void* p) { asm volatile("prefetch.global.L2 [%0];" ::"l"(p)); }
__device__ __forceinline__ uint32_t ldcg32(const void* p) { uint32_t v; asm volatile("ld.global.cg.b32 %0, [%1];" : "=r"(v) : "l"(p) : "memory"); return v; }
__device__ __forceinline__ uint4 ldcg128(const void* p) { uint4 v; asm volatile("ld.global.cg.v4.b32 {%0,%1,%2,%3}, [%4];" : "=r"(v.x), "=r"(v.y), "=r"(v.z), "=r"(v.w) : "l"(p) : "memory"); return v; }

template<int O, int M> __device__ __forceinline__ void mma_n128(float (&d)[M], uint64_t da, uint64_t db, int sd) {
  asm volatile("{\n.reg .pred p;\nsetp.ne.b32 p, %66, 0;\n"
    "wgmma.mma_async.sync.aligned.m64n128k16.f32.bf16.bf16 {%0, %1, %2, %3, %4, %5, %6, %7, %8, %9, %10, %11, %12, %13, %14, %15, %16, %17, %18, %19, %20, %21, %22, %23, %24, %25, %26, %27, %28, %29, %30, %31, %32, %33, %34, %35, %36, %37, %38, %39, %40, %41, %42, %43, %44, %45, %46, %47, %48, %49, %50, %51, %52, %53, %54, %55, %56, %57, %58, %59, %60, %61, %62, %63}, %64, %65, p, 1, 1, 0, 1;\n}\n"
    : "+f"(d[O+0]), "+f"(d[O+1]), "+f"(d[O+2]), "+f"(d[O+3]), "+f"(d[O+4]), "+f"(d[O+5]), "+f"(d[O+6]), "+f"(d[O+7]), "+f"(d[O+8]), "+f"(d[O+9]), "+f"(d[O+10]), "+f"(d[O+11]), "+f"(d[O+12]), "+f"(d[O+13]), "+f"(d[O+14]), "+f"(d[O+15]), "+f"(d[O+16]), "+f"(d[O+17]), "+f"(d[O+18]), "+f"(d[O+19]), "+f"(d[O+20]), "+f"(d[O+21]), "+f"(d[O+22]), "+f"(d[O+23]), "+f"(d[O+24]), "+f"(d[O+25]), "+f"(d[O+26]), "+f"(d[O+27]), "+f"(d[O+28]), "+f"(d[O+29]), "+f"(d[O+30]), "+f"(d[O+31]), "+f"(d[O+32]), "+f"(d[O+33]), "+f"(d[O+34]), "+f"(d[O+35]), "+f"(d[O+36]), "+f"(d[O+37]), "+f"(d[O+38]), "+f"(d[O+39]), "+f"(d[O+40]), "+f"(d[O+41]), "+f"(d[O+42]), "+f"(d[O+43]), "+f"(d[O+44]), "+f"(d[O+45]), "+f"(d[O+46]), "+f"(d[O+47]), "+f"(d[O+48]), "+f"(d[O+49]), "+f"(d[O+50]), "+f"(d[O+51]), "+f"(d[O+52]), "+f"(d[O+53]), "+f"(d[O+54]), "+f"(d[O+55]), "+f"(d[O+56]), "+f"(d[O+57]), "+f"(d[O+58]), "+f"(d[O+59]), "+f"(d[O+60]), "+f"(d[O+61]), "+f"(d[O+62]), "+f"(d[O+63])
    : "l"(da), "l"(db), "r"(sd));
}
template<int O, int M> __device__ __forceinline__ void mma_n128_ext(float (&d)[M], uint32_t a0, uint32_t a1, uint64_t db) {
  asm volatile("{\n.reg .pred p;\nsetp.eq.b32 p, 0, 0;\n"
    "wgmma.mma_async.sync.aligned.m64n128k16.f32.bf16.bf16 {%0, %1, %2, %3, %4, %5, %6, %7, %8, %9, %10, %11, %12, %13, %14, %15, %16, %17, %18, %19, %20, %21, %22, %23, %24, %25, %26, %27, %28, %29, %30, %31, %32, %33, %34, %35, %36, %37, %38, %39, %40, %41, %42, %43, %44, %45, %46, %47, %48, %49, %50, %51, %52, %53, %54, %55, %56, %57, %58, %59, %60, %61, %62, %63}, {%64,%65,%66,%66}, %67, p, 1, 1, 0;\n}\n"
    : "+f"(d[O+0]), "+f"(d[O+1]), "+f"(d[O+2]), "+f"(d[O+3]), "+f"(d[O+4]), "+f"(d[O+5]), "+f"(d[O+6]), "+f"(d[O+7]), "+f"(d[O+8]), "+f"(d[O+9]), "+f"(d[O+10]), "+f"(d[O+11]), "+f"(d[O+12]), "+f"(d[O+13]), "+f"(d[O+14]), "+f"(d[O+15]), "+f"(d[O+16]), "+f"(d[O+17]), "+f"(d[O+18]), "+f"(d[O+19]), "+f"(d[O+20]), "+f"(d[O+21]), "+f"(d[O+22]), "+f"(d[O+23]), "+f"(d[O+24]), "+f"(d[O+25]), "+f"(d[O+26]), "+f"(d[O+27]), "+f"(d[O+28]), "+f"(d[O+29]), "+f"(d[O+30]), "+f"(d[O+31]), "+f"(d[O+32]), "+f"(d[O+33]), "+f"(d[O+34]), "+f"(d[O+35]), "+f"(d[O+36]), "+f"(d[O+37]), "+f"(d[O+38]), "+f"(d[O+39]), "+f"(d[O+40]), "+f"(d[O+41]), "+f"(d[O+42]), "+f"(d[O+43]), "+f"(d[O+44]), "+f"(d[O+45]), "+f"(d[O+46]), "+f"(d[O+47]), "+f"(d[O+48]), "+f"(d[O+49]), "+f"(d[O+50]), "+f"(d[O+51]), "+f"(d[O+52]), "+f"(d[O+53]), "+f"(d[O+54]), "+f"(d[O+55]), "+f"(d[O+56]), "+f"(d[O+57]), "+f"(d[O+58]), "+f"(d[O+59]), "+f"(d[O+60]), "+f"(d[O+61]), "+f"(d[O+62]), "+f"(d[O+63])
    : "r"(a0), "r"(a1), "r"(0), "l"(db));
}
template<int M> __device__ __forceinline__ void mma_n192(float (&d)[M], uint64_t da, uint64_t db, int sd) {
  asm volatile("{\n.reg .pred p;\nsetp.ne.b32 p, %98, 0;\n"
    "wgmma.mma_async.sync.aligned.m64n192k16.f32.bf16.bf16 {%0, %1, %2, %3, %4, %5, %6, %7, %8, %9, %10, %11, %12, %13, %14, %15, %16, %17, %18, %19, %20, %21, %22, %23, %24, %25, %26, %27, %28, %29, %30, %31, %32, %33, %34, %35, %36, %37, %38, %39, %40, %41, %42, %43, %44, %45, %46, %47, %48, %49, %50, %51, %52, %53, %54, %55, %56, %57, %58, %59, %60, %61, %62, %63, %64, %65, %66, %67, %68, %69, %70, %71, %72, %73, %74, %75, %76, %77, %78, %79, %80, %81, %82, %83, %84, %85, %86, %87, %88, %89, %90, %91, %92, %93, %94, %95}, %96, %97, p, 1, 1, 0, 1;\n}\n"
    : "+f"(d[0]), "+f"(d[1]), "+f"(d[2]), "+f"(d[3]), "+f"(d[4]), "+f"(d[5]), "+f"(d[6]), "+f"(d[7]), "+f"(d[8]), "+f"(d[9]), "+f"(d[10]), "+f"(d[11]), "+f"(d[12]), "+f"(d[13]), "+f"(d[14]), "+f"(d[15]), "+f"(d[16]), "+f"(d[17]), "+f"(d[18]), "+f"(d[19]), "+f"(d[20]), "+f"(d[21]), "+f"(d[22]), "+f"(d[23]), "+f"(d[24]), "+f"(d[25]), "+f"(d[26]), "+f"(d[27]), "+f"(d[28]), "+f"(d[29]), "+f"(d[30]), "+f"(d[31]), "+f"(d[32]), "+f"(d[33]), "+f"(d[34]), "+f"(d[35]), "+f"(d[36]), "+f"(d[37]), "+f"(d[38]), "+f"(d[39]), "+f"(d[40]), "+f"(d[41]), "+f"(d[42]), "+f"(d[43]), "+f"(d[44]), "+f"(d[45]), "+f"(d[46]), "+f"(d[47]), "+f"(d[48]), "+f"(d[49]), "+f"(d[50]), "+f"(d[51]), "+f"(d[52]), "+f"(d[53]), "+f"(d[54]), "+f"(d[55]), "+f"(d[56]), "+f"(d[57]), "+f"(d[58]), "+f"(d[59]), "+f"(d[60]), "+f"(d[61]), "+f"(d[62]), "+f"(d[63]), "+f"(d[64]), "+f"(d[65]), "+f"(d[66]), "+f"(d[67]), "+f"(d[68]), "+f"(d[69]), "+f"(d[70]), "+f"(d[71]), "+f"(d[72]), "+f"(d[73]), "+f"(d[74]), "+f"(d[75]), "+f"(d[76]), "+f"(d[77]), "+f"(d[78]), "+f"(d[79]), "+f"(d[80]), "+f"(d[81]), "+f"(d[82]), "+f"(d[83]), "+f"(d[84]), "+f"(d[85]), "+f"(d[86]), "+f"(d[87]), "+f"(d[88]), "+f"(d[89]), "+f"(d[90]), "+f"(d[91]), "+f"(d[92]), "+f"(d[93]), "+f"(d[94]), "+f"(d[95])
    : "l"(da), "l"(db), "r"(sd));
}
template<int O, int M> __device__ __forceinline__ void mma_n192_ext(float (&d)[M], uint32_t a0, uint32_t a1, uint64_t db) {
  asm volatile("{\n.reg .pred p;\nsetp.eq.b32 p, 0, 0;\n"
    "wgmma.mma_async.sync.aligned.m64n192k16.f32.bf16.bf16 {%0, %1, %2, %3, %4, %5, %6, %7, %8, %9, %10, %11, %12, %13, %14, %15, %16, %17, %18, %19, %20, %21, %22, %23, %24, %25, %26, %27, %28, %29, %30, %31, %32, %33, %34, %35, %36, %37, %38, %39, %40, %41, %42, %43, %44, %45, %46, %47, %48, %49, %50, %51, %52, %53, %54, %55, %56, %57, %58, %59, %60, %61, %62, %63, %64, %65, %66, %67, %68, %69, %70, %71, %72, %73, %74, %75, %76, %77, %78, %79, %80, %81, %82, %83, %84, %85, %86, %87, %88, %89, %90, %91, %92, %93, %94, %95}, {%96,%97,%98,%98}, %99, p, 1, 1, 0;\n}\n"
    : "+f"(d[O+0]), "+f"(d[O+1]), "+f"(d[O+2]), "+f"(d[O+3]), "+f"(d[O+4]), "+f"(d[O+5]), "+f"(d[O+6]), "+f"(d[O+7]), "+f"(d[O+8]), "+f"(d[O+9]), "+f"(d[O+10]), "+f"(d[O+11]), "+f"(d[O+12]), "+f"(d[O+13]), "+f"(d[O+14]), "+f"(d[O+15]), "+f"(d[O+16]), "+f"(d[O+17]), "+f"(d[O+18]), "+f"(d[O+19]), "+f"(d[O+20]), "+f"(d[O+21]), "+f"(d[O+22]), "+f"(d[O+23]), "+f"(d[O+24]), "+f"(d[O+25]), "+f"(d[O+26]), "+f"(d[O+27]), "+f"(d[O+28]), "+f"(d[O+29]), "+f"(d[O+30]), "+f"(d[O+31]), "+f"(d[O+32]), "+f"(d[O+33]), "+f"(d[O+34]), "+f"(d[O+35]), "+f"(d[O+36]), "+f"(d[O+37]), "+f"(d[O+38]), "+f"(d[O+39]), "+f"(d[O+40]), "+f"(d[O+41]), "+f"(d[O+42]), "+f"(d[O+43]), "+f"(d[O+44]), "+f"(d[O+45]), "+f"(d[O+46]), "+f"(d[O+47]), "+f"(d[O+48]), "+f"(d[O+49]), "+f"(d[O+50]), "+f"(d[O+51]), "+f"(d[O+52]), "+f"(d[O+53]), "+f"(d[O+54]), "+f"(d[O+55]), "+f"(d[O+56]), "+f"(d[O+57]), "+f"(d[O+58]), "+f"(d[O+59]), "+f"(d[O+60]), "+f"(d[O+61]), "+f"(d[O+62]), "+f"(d[O+63]), "+f"(d[O+64]), "+f"(d[O+65]), "+f"(d[O+66]), "+f"(d[O+67]), "+f"(d[O+68]), "+f"(d[O+69]), "+f"(d[O+70]), "+f"(d[O+71]), "+f"(d[O+72]), "+f"(d[O+73]), "+f"(d[O+74]), "+f"(d[O+75]), "+f"(d[O+76]), "+f"(d[O+77]), "+f"(d[O+78]), "+f"(d[O+79]), "+f"(d[O+80]), "+f"(d[O+81]), "+f"(d[O+82]), "+f"(d[O+83]), "+f"(d[O+84]), "+f"(d[O+85]), "+f"(d[O+86]), "+f"(d[O+87]), "+f"(d[O+88]), "+f"(d[O+89]), "+f"(d[O+90]), "+f"(d[O+91]), "+f"(d[O+92]), "+f"(d[O+93]), "+f"(d[O+94]), "+f"(d[O+95])
    : "r"(a0), "r"(a1), "r"(0), "l"(db));
}
template<int M> __device__ __forceinline__ void mma_n160(float (&d)[M], uint64_t da, uint64_t db, int sd) {
  asm volatile("{\n.reg .pred p;\nsetp.ne.b32 p, %82, 0;\n"
    "wgmma.mma_async.sync.aligned.m64n160k16.f32.bf16.bf16 {%0, %1, %2, %3, %4, %5, %6, %7, %8, %9, %10, %11, %12, %13, %14, %15, %16, %17, %18, %19, %20, %21, %22, %23, %24, %25, %26, %27, %28, %29, %30, %31, %32, %33, %34, %35, %36, %37, %38, %39, %40, %41, %42, %43, %44, %45, %46, %47, %48, %49, %50, %51, %52, %53, %54, %55, %56, %57, %58, %59, %60, %61, %62, %63, %64, %65, %66, %67, %68, %69, %70, %71, %72, %73, %74, %75, %76, %77, %78, %79}, %80, %81, p, 1, 1, 0, 1;\n}\n"
    : "+f"(d[0]), "+f"(d[1]), "+f"(d[2]), "+f"(d[3]), "+f"(d[4]), "+f"(d[5]), "+f"(d[6]), "+f"(d[7]), "+f"(d[8]), "+f"(d[9]), "+f"(d[10]), "+f"(d[11]), "+f"(d[12]), "+f"(d[13]), "+f"(d[14]), "+f"(d[15]), "+f"(d[16]), "+f"(d[17]), "+f"(d[18]), "+f"(d[19]), "+f"(d[20]), "+f"(d[21]), "+f"(d[22]), "+f"(d[23]), "+f"(d[24]), "+f"(d[25]), "+f"(d[26]), "+f"(d[27]), "+f"(d[28]), "+f"(d[29]), "+f"(d[30]), "+f"(d[31]), "+f"(d[32]), "+f"(d[33]), "+f"(d[34]), "+f"(d[35]), "+f"(d[36]), "+f"(d[37]), "+f"(d[38]), "+f"(d[39]), "+f"(d[40]), "+f"(d[41]), "+f"(d[42]), "+f"(d[43]), "+f"(d[44]), "+f"(d[45]), "+f"(d[46]), "+f"(d[47]), "+f"(d[48]), "+f"(d[49]), "+f"(d[50]), "+f"(d[51]), "+f"(d[52]), "+f"(d[53]), "+f"(d[54]), "+f"(d[55]), "+f"(d[56]), "+f"(d[57]), "+f"(d[58]), "+f"(d[59]), "+f"(d[60]), "+f"(d[61]), "+f"(d[62]), "+f"(d[63]), "+f"(d[64]), "+f"(d[65]), "+f"(d[66]), "+f"(d[67]), "+f"(d[68]), "+f"(d[69]), "+f"(d[70]), "+f"(d[71]), "+f"(d[72]), "+f"(d[73]), "+f"(d[74]), "+f"(d[75]), "+f"(d[76]), "+f"(d[77]), "+f"(d[78]), "+f"(d[79])
    : "l"(da), "l"(db), "r"(sd));
}
template<int O, int M> __device__ __forceinline__ void mma_h80(float (&d)[M], uint64_t da, uint64_t db, int sd) {
  asm volatile("{\n.reg .pred p;\nsetp.ne.b32 p, %42, 0;\n"
    "wgmma.mma_async.sync.aligned.m64n80k16.f32.f16.f16 {%0, %1, %2, %3, %4, %5, %6, %7, %8, %9, %10, %11, %12, %13, %14, %15, %16, %17, %18, %19, %20, %21, %22, %23, %24, %25, %26, %27, %28, %29, %30, %31, %32, %33, %34, %35, %36, %37, %38, %39}, %40, %41, p, 1, 1, 0, 0;\n}\n"
    : "+f"(d[O+0]), "+f"(d[O+1]), "+f"(d[O+2]), "+f"(d[O+3]), "+f"(d[O+4]), "+f"(d[O+5]), "+f"(d[O+6]), "+f"(d[O+7]), "+f"(d[O+8]), "+f"(d[O+9]), "+f"(d[O+10]), "+f"(d[O+11]), "+f"(d[O+12]), "+f"(d[O+13]), "+f"(d[O+14]), "+f"(d[O+15]), "+f"(d[O+16]), "+f"(d[O+17]), "+f"(d[O+18]), "+f"(d[O+19]), "+f"(d[O+20]), "+f"(d[O+21]), "+f"(d[O+22]), "+f"(d[O+23]), "+f"(d[O+24]), "+f"(d[O+25]), "+f"(d[O+26]), "+f"(d[O+27]), "+f"(d[O+28]), "+f"(d[O+29]), "+f"(d[O+30]), "+f"(d[O+31]), "+f"(d[O+32]), "+f"(d[O+33]), "+f"(d[O+34]), "+f"(d[O+35]), "+f"(d[O+36]), "+f"(d[O+37]), "+f"(d[O+38]), "+f"(d[O+39])
    : "l"(da), "l"(db), "r"(sd));
}
template<int O, int M> __device__ __forceinline__ void mma_h80_neg(float (&d)[M], uint64_t da, uint64_t db, int sd) {
  asm volatile("{\n.reg .pred p;\nsetp.ne.b32 p, %42, 0;\n"
    "wgmma.mma_async.sync.aligned.m64n80k16.f32.f16.f16 {%0, %1, %2, %3, %4, %5, %6, %7, %8, %9, %10, %11, %12, %13, %14, %15, %16, %17, %18, %19, %20, %21, %22, %23, %24, %25, %26, %27, %28, %29, %30, %31, %32, %33, %34, %35, %36, %37, %38, %39}, %40, %41, p, -1, 1, 0, 0;\n}\n"
    : "+f"(d[O+0]), "+f"(d[O+1]), "+f"(d[O+2]), "+f"(d[O+3]), "+f"(d[O+4]), "+f"(d[O+5]), "+f"(d[O+6]), "+f"(d[O+7]), "+f"(d[O+8]), "+f"(d[O+9]), "+f"(d[O+10]), "+f"(d[O+11]), "+f"(d[O+12]), "+f"(d[O+13]), "+f"(d[O+14]), "+f"(d[O+15]), "+f"(d[O+16]), "+f"(d[O+17]), "+f"(d[O+18]), "+f"(d[O+19]), "+f"(d[O+20]), "+f"(d[O+21]), "+f"(d[O+22]), "+f"(d[O+23]), "+f"(d[O+24]), "+f"(d[O+25]), "+f"(d[O+26]), "+f"(d[O+27]), "+f"(d[O+28]), "+f"(d[O+29]), "+f"(d[O+30]), "+f"(d[O+31]), "+f"(d[O+32]), "+f"(d[O+33]), "+f"(d[O+34]), "+f"(d[O+35]), "+f"(d[O+36]), "+f"(d[O+37]), "+f"(d[O+38]), "+f"(d[O+39])
    : "l"(da), "l"(db), "r"(sd));
}
template<int O, int M> __device__ __forceinline__ void mma_n32t(float (&d)[M], uint64_t da, uint64_t db, int sd) {
  asm volatile("{\n.reg .pred p;\nsetp.ne.b32 p, %18, 0;\n"
    "wgmma.mma_async.sync.aligned.m64n32k16.f32.f16.f16 {%0, %1, %2, %3, %4, %5, %6, %7, %8, %9, %10, %11, %12, %13, %14, %15}, %16, %17, p, 1, 1, 1, 0;\n}\n"
    : "+f"(d[O+0]), "+f"(d[O+1]), "+f"(d[O+2]), "+f"(d[O+3]), "+f"(d[O+4]), "+f"(d[O+5]), "+f"(d[O+6]), "+f"(d[O+7]), "+f"(d[O+8]), "+f"(d[O+9]), "+f"(d[O+10]), "+f"(d[O+11]), "+f"(d[O+12]), "+f"(d[O+13]), "+f"(d[O+14]), "+f"(d[O+15])
    : "l"(da), "l"(db), "r"(sd));
}
template<int O, int M> __device__ __forceinline__ void mma_n192_first(float (&d)[M], uint64_t da, uint64_t db) {
  asm volatile("{\n.reg .pred p;\nsetp.ne.b32 p, 0, 0;\n"
    "wgmma.mma_async.sync.aligned.m64n192k16.f32.bf16.bf16 {%0, %1, %2, %3, %4, %5, %6, %7, %8, %9, %10, %11, %12, %13, %14, %15, %16, %17, %18, %19, %20, %21, %22, %23, %24, %25, %26, %27, %28, %29, %30, %31, %32, %33, %34, %35, %36, %37, %38, %39, %40, %41, %42, %43, %44, %45, %46, %47, %48, %49, %50, %51, %52, %53, %54, %55, %56, %57, %58, %59, %60, %61, %62, %63, %64, %65, %66, %67, %68, %69, %70, %71, %72, %73, %74, %75, %76, %77, %78, %79, %80, %81, %82, %83, %84, %85, %86, %87, %88, %89, %90, %91, %92, %93, %94, %95}, %96, %97, p, 1, 1, 0, 1;\n}\n"
    : "=f"(d[O+0]), "=f"(d[O+1]), "=f"(d[O+2]), "=f"(d[O+3]), "=f"(d[O+4]), "=f"(d[O+5]), "=f"(d[O+6]), "=f"(d[O+7]), "=f"(d[O+8]), "=f"(d[O+9]), "=f"(d[O+10]), "=f"(d[O+11]), "=f"(d[O+12]), "=f"(d[O+13]), "=f"(d[O+14]), "=f"(d[O+15]), "=f"(d[O+16]), "=f"(d[O+17]), "=f"(d[O+18]), "=f"(d[O+19]), "=f"(d[O+20]), "=f"(d[O+21]), "=f"(d[O+22]), "=f"(d[O+23]), "=f"(d[O+24]), "=f"(d[O+25]), "=f"(d[O+26]), "=f"(d[O+27]), "=f"(d[O+28]), "=f"(d[O+29]), "=f"(d[O+30]), "=f"(d[O+31]), "=f"(d[O+32]), "=f"(d[O+33]), "=f"(d[O+34]), "=f"(d[O+35]), "=f"(d[O+36]), "=f"(d[O+37]), "=f"(d[O+38]), "=f"(d[O+39]), "=f"(d[O+40]), "=f"(d[O+41]), "=f"(d[O+42]), "=f"(d[O+43]), "=f"(d[O+44]), "=f"(d[O+45]), "=f"(d[O+46]), "=f"(d[O+47]), "=f"(d[O+48]), "=f"(d[O+49]), "=f"(d[O+50]), "=f"(d[O+51]), "=f"(d[O+52]), "=f"(d[O+53]), "=f"(d[O+54]), "=f"(d[O+55]), "=f"(d[O+56]), "=f"(d[O+57]), "=f"(d[O+58]), "=f"(d[O+59]), "=f"(d[O+60]), "=f"(d[O+61]), "=f"(d[O+62]), "=f"(d[O+63]), "=f"(d[O+64]), "=f"(d[O+65]), "=f"(d[O+66]), "=f"(d[O+67]), "=f"(d[O+68]), "=f"(d[O+69]), "=f"(d[O+70]), "=f"(d[O+71]), "=f"(d[O+72]), "=f"(d[O+73]), "=f"(d[O+74]), "=f"(d[O+75]), "=f"(d[O+76]), "=f"(d[O+77]), "=f"(d[O+78]), "=f"(d[O+79]), "=f"(d[O+80]), "=f"(d[O+81]), "=f"(d[O+82]), "=f"(d[O+83]), "=f"(d[O+84]), "=f"(d[O+85]), "=f"(d[O+86]), "=f"(d[O+87]), "=f"(d[O+88]), "=f"(d[O+89]), "=f"(d[O+90]), "=f"(d[O+91]), "=f"(d[O+92]), "=f"(d[O+93]), "=f"(d[O+94]), "=f"(d[O+95])
    : "l"(da), "l"(db));
}
template<int O, int M> __device__ __forceinline__ void mma_n160_first(float (&d)[M], uint64_t da, uint64_t db) {
  asm volatile("{\n.reg .pred p;\nsetp.ne.b32 p, 0, 0;\n"
    "wgmma.mma_async.sync.aligned.m64n160k16.f32.bf16.bf16 {%0, %1, %2, %3, %4, %5, %6, %7, %8, %9, %10, %11, %12, %13, %14, %15, %16, %17, %18, %19, %20, %21, %22, %23, %24, %25, %26, %27, %28, %29, %30, %31, %32, %33, %34, %35, %36, %37, %38, %39, %40, %41, %42, %43, %44, %45, %46, %47, %48, %49, %50, %51, %52, %53, %54, %55, %56, %57, %58, %59, %60, %61, %62, %63, %64, %65, %66, %67, %68, %69, %70, %71, %72, %73, %74, %75, %76, %77, %78, %79}, %80, %81, p, 1, 1, 0, 1;\n}\n"
    : "=f"(d[O+0]), "=f"(d[O+1]), "=f"(d[O+2]), "=f"(d[O+3]), "=f"(d[O+4]), "=f"(d[O+5]), "=f"(d[O+6]), "=f"(d[O+7]), "=f"(d[O+8]), "=f"(d[O+9]), "=f"(d[O+10]), "=f"(d[O+11]), "=f"(d[O+12]), "=f"(d[O+13]), "=f"(d[O+14]), "=f"(d[O+15]), "=f"(d[O+16]), "=f"(d[O+17]), "=f"(d[O+18]), "=f"(d[O+19]), "=f"(d[O+20]), "=f"(d[O+21]), "=f"(d[O+22]), "=f"(d[O+23]), "=f"(d[O+24]), "=f"(d[O+25]), "=f"(d[O+26]), "=f"(d[O+27]), "=f"(d[O+28]), "=f"(d[O+29]), "=f"(d[O+30]), "=f"(d[O+31]), "=f"(d[O+32]), "=f"(d[O+33]), "=f"(d[O+34]), "=f"(d[O+35]), "=f"(d[O+36]), "=f"(d[O+37]), "=f"(d[O+38]), "=f"(d[O+39]), "=f"(d[O+40]), "=f"(d[O+41]), "=f"(d[O+42]), "=f"(d[O+43]), "=f"(d[O+44]), "=f"(d[O+45]), "=f"(d[O+46]), "=f"(d[O+47]), "=f"(d[O+48]), "=f"(d[O+49]), "=f"(d[O+50]), "=f"(d[O+51]), "=f"(d[O+52]), "=f"(d[O+53]), "=f"(d[O+54]), "=f"(d[O+55]), "=f"(d[O+56]), "=f"(d[O+57]), "=f"(d[O+58]), "=f"(d[O+59]), "=f"(d[O+60]), "=f"(d[O+61]), "=f"(d[O+62]), "=f"(d[O+63]), "=f"(d[O+64]), "=f"(d[O+65]), "=f"(d[O+66]), "=f"(d[O+67]), "=f"(d[O+68]), "=f"(d[O+69]), "=f"(d[O+70]), "=f"(d[O+71]), "=f"(d[O+72]), "=f"(d[O+73]), "=f"(d[O+74]), "=f"(d[O+75]), "=f"(d[O+76]), "=f"(d[O+77]), "=f"(d[O+78]), "=f"(d[O+79])
    : "l"(da), "l"(db));
}
template<int O, int M> __device__ __forceinline__ void mma_n32t_first(float (&d)[M], uint64_t da, uint64_t db) {
  asm volatile("{\n.reg .pred p;\nsetp.ne.b32 p, 0, 0;\n"
    "wgmma.mma_async.sync.aligned.m64n32k16.f32.f16.f16 {%0, %1, %2, %3, %4, %5, %6, %7, %8, %9, %10, %11, %12, %13, %14, %15}, %16, %17, p, 1, 1, 1, 0;\n}\n"
    : "=f"(d[O+0]), "=f"(d[O+1]), "=f"(d[O+2]), "=f"(d[O+3]), "=f"(d[O+4]), "=f"(d[O+5]), "=f"(d[O+6]), "=f"(d[O+7]), "=f"(d[O+8]), "=f"(d[O+9]), "=f"(d[O+10]), "=f"(d[O+11]), "=f"(d[O+12]), "=f"(d[O+13]), "=f"(d[O+14]), "=f"(d[O+15])
    : "l"(da), "l"(db));
}

__device__ __forceinline__ float2 cmul(float2 a, float2 b) { return make_float2(fmaf(a.x, b.x, -a.y * b.y), fmaf(a.x, b.y, a.y * b.x)); }
struct C2 { __half2 x, y; };
__device__ __forceinline__ C2 cadd(C2 a, C2 b) { return {__hadd2(a.x, b.x), __hadd2(a.y, b.y)}; }
__device__ __forceinline__ C2 csub(C2 a, C2 b) { return {__hsub2(a.x, b.x), __hsub2(a.y, b.y)}; }
__device__ __forceinline__ C2 cmulh(C2 a, __half2 c, __half2 s) { return {__hfma2(a.x, c, __hneg2(__hmul2(a.y, s))), __hfma2(a.x, s, __hmul2(a.y, c))}; }
__host__ __device__ constexpr double cos64(int j) {
  return j == 0 ? 1.0 : j == 1 ? 0.99518472667219689 : j == 2 ? 0.98078528040323045 : j == 3 ? 0.95694033573220887 : j == 4 ? 0.92387953251128676 :
         j == 5 ? 0.88192126434835503 : j == 6 ? 0.83146961230254524 : j == 7 ? 0.77301045336273696 : j == 8 ? 0.70710678118654752 :
         j == 9 ? 0.63439328416364550 : j == 10 ? 0.55557023301960222 : j == 11 ? 0.47139673682599765 : j == 12 ? 0.38268343236508977 :
         j == 13 ? 0.29028467725446237 : j == 14 ? 0.19509032201612827 : j == 15 ? 0.09801714032956060 : 0.0;
}
template <int J> __device__ __forceinline__ C2 mulw64(C2 a) {
  constexpr int r = J & 15, qd = (J >> 4) & 3;
  C2 t = a;
  if (r == 8) { const __half2 h = __float2half2_rn(0.70710678118654752f); t = {__hmul2(__hadd2(a.x, a.y), h), __hmul2(__hsub2(a.y, a.x), h)}; }
  else if (r != 0) t = cmulh(a, __float2half2_rn((float)cos64(r)), __float2half2_rn((float)-cos64(16 - r)));
  if (qd == 1) return {t.y, __hneg2(t.x)};
  if (qd == 2) return {__hneg2(t.x), __hneg2(t.y)};
  if (qd == 3) return {__hneg2(t.y), t.x};
  return t;
}
__device__ __forceinline__ void dft4(C2& a, C2& b, C2& c, C2& d) {
  const C2 t0 = cadd(a, c), t1 = csub(a, c), t2 = cadd(b, d), t3 = csub(b, d);
  a = cadd(t0, t2); c = csub(t0, t2);
  b = {__hadd2(t1.x, t3.y), __hsub2(t1.y, t3.x)}; d = {__hsub2(t1.x, t3.y), __hadd2(t1.y, t3.x)};
}
template <int O> __device__ __forceinline__ void dft8(C2 (&x)[16]) {
#pragma unroll
  for (int n = 0; n < 4; n++) { const C2 a = x[O + n], b = x[O + 4 + n]; x[O + n] = cadd(a, b); x[O + 4 + n] = csub(a, b); }
  x[O + 5] = mulw64<8>(x[O + 5]); x[O + 6] = mulw64<16>(x[O + 6]); x[O + 7] = mulw64<24>(x[O + 7]);
  dft4(x[O], x[O + 1], x[O + 2], x[O + 3]); dft4(x[O + 4], x[O + 5], x[O + 6], x[O + 7]);
}
__device__ __forceinline__ void dft16(C2 (&x)[16]) {
#pragma unroll
  for (int n = 0; n < 4; n++) dft4(x[n], x[4 + n], x[8 + n], x[12 + n]);
  x[5] = mulw64<4>(x[5]); x[6] = mulw64<8>(x[6]); x[7] = mulw64<12>(x[7]);
  x[9] = mulw64<8>(x[9]); x[10] = mulw64<16>(x[10]); x[11] = mulw64<24>(x[11]);
  x[13] = mulw64<12>(x[13]); x[14] = mulw64<24>(x[14]); x[15] = mulw64<36>(x[15]);
#pragma unroll
  for (int k = 0; k < 4; k++) dft4(x[4 * k], x[4 * k + 1], x[4 * k + 2], x[4 * k + 3]);
}
template <int STRIDE, int XOR> __device__ __forceinline__ void twiddle_store(const C2 (&x)[16], const __half2 (&tw)[16], uint32_t addr) {
#pragma unroll
  for (int k = 0; k < 16; k++) {
    const C2 a = x[4 * (k & 3) + (k >> 2)];
    const C2 t = k ? cmulh(a, __low2half2(tw[k]), __high2half2(tw[k])) : C2{__hmul2(a.x, tw[0]), __hmul2(a.y, tw[0])};
    sts64((addr ^ (k * XOR)) + k * STRIDE, h2u(t.x), h2u(t.y));
  }
}
__device__ __forceinline__ void twiddle_load(__half2 (&tw)[16], const uint32_t* p, int stride) {
#pragma unroll
  for (int i = 0; i < 4; i++) { const uint4 v = __ldg((const uint4*)p + i * stride); tw[4 * i] = u2h(v.x); tw[4 * i + 1] = u2h(v.y); tw[4 * i + 2] = u2h(v.z); tw[4 * i + 3] = u2h(v.w); }
}

__device__ __forceinline__ void h_store(uint8_t* dst, uint4 a, uint4 b) { stg128(dst, a.x, a.y, a.z, a.w); stg128(dst + 512, b.x, b.y, b.z, b.w); }
template <int BG, int BU, int RH, int M>
__device__ __forceinline__ uint4 h_unit(const uint32_t (&pk)[M], float hr) {
  uint32_t w[4];
#pragma unroll
  for (int a = 0; a < 4; a++) {
    const uint32_t g2 = pk[(BG + a) * 2 + RH];
    const float t0 = tanh_fast(bf_lo(g2) * hr), t1 = tanh_fast(bf_hi(g2) * hr);
    w[a] = hmul2_bf(pack_bf16(fmaf(t0, hr, hr), fmaf(t1, hr, hr)), pk[(BU + a) * 2 + RH]);
  }
  return make_uint4(w[0], w[1], w[2], w[3]);
}

template <int BG, int BU, int RH, int M>
__device__ __forceinline__ uint4 h_unit_acc(const float (&acc)[M], float hr) {
  uint32_t w[4];
#pragma unroll
  for (int a = 0; a < 4; a++) {
    const int ig = (BG + a) * 4 + 2 * RH, iu = (BU + a) * 4 + 2 * RH;
    const float t0 = tanh_fast(acc[ig] * hr), t1 = tanh_fast(acc[ig + 1] * hr);
    w[a] = hmul2_bf(pack_bf16(fmaf(t0, hr, hr), fmaf(t1, hr, hr)), pack_bf16(acc[iu], acc[iu + 1]));
  }
  return make_uint4(w[0], w[1], w[2], w[3]);
}

template <int N> __device__ __forceinline__ void fold(float* a, int lane, int bit) {
#pragma unroll
  for (int k = 0; k < N; k++) {
    const bool up = lane & bit;
    const float t = __shfl_xor_sync(~0u, up ? a[k] : a[k + N], bit);
    a[k] = (up ? a[k + N] : a[k]) + t;
  }
}
template <int N> __device__ __forceinline__ void cs_load(uint4 (&cv)[N], const __nv_bfloat16* w, int tid) {
  const uint4* p = (const uint4*)(w + (size_t)(tid >> 3) * F_) + (tid & 7);
#pragma unroll
  for (int i = 0; i < N; i++) asm volatile("ld.global.nc.v4.b32 {%0,%1,%2,%3}, [%4];" : "=r"(cv[i].x), "=r"(cv[i].y), "=r"(cv[i].z), "=r"(cv[i].w) : "l"(p + (size_t)i * 16 * (F_ / 8)) : "memory");
}
template <int N> __device__ __forceinline__ void cs_finish(const uint4 (&cv)[N], uint2* dst, uint32_t sb, unsigned ep1, int tid) {
  float a[8];
#pragma unroll
  for (int i = 0; i < N; i += 2) {
    const uint32_t wv[4] = {hadd2_bf(cv[i].x, cv[i + 1].x), hadd2_bf(cv[i].y, cv[i + 1].y), hadd2_bf(cv[i].z, cv[i + 1].z), hadd2_bf(cv[i].w, cv[i + 1].w)};
#pragma unroll
    for (int k = 0; k < 4; k++) { a[2 * k] = i ? a[2 * k] + bf_lo(wv[k]) : bf_lo(wv[k]); a[2 * k + 1] = i ? a[2 * k + 1] + bf_hi(wv[k]) : bf_hi(wv[k]); }
  }
  const int lane = tid & 31;
  fold<4>(a, lane, 8); fold<2>(a, lane, 16);
  if (N == 8) sb -= 1536;
  sts64(sb + CSRED + (tid >> 5) * 256 + ((lane & 7) * 8 + ((lane >> 3) & 1) * 4 + (lane >> 4) * 2) * 4, __float_as_uint(a[0]), __float_as_uint(a[1]));
  bar_sync(1, 128);
  if (tid < 64) {
    const uint32_t a0 = sb + CSRED + tid * 4;
    st_tag(dst + tid, __float_as_uint((__uint_as_float(lds32(a0)) + __uint_as_float(lds32(a0 + 256))) + (__uint_as_float(lds32(a0 + 512)) + __uint_as_float(lds32(a0 + 768)))), ep1);
  }
}
__device__ __forceinline__ int zpos(int k) { const int j = k >> 2; return (k & 3) * 80 + (j & ~7) + (j & 1) * 4 + ((j >> 1) & 3); }
__device__ __forceinline__ void z_fetch(const Params& P, uint32_t sb, int k) {
  e_expect(sb + B_ZIN, 16384);
  e_tma3d(sb + ZIN, &P.mz, sb + B_ZIN, 0, zpos(k));
  e_tma3d(sb + ZIN + 8192, &P.mz, sb + B_ZIN, 0, zpos(k ? 320 - k : 0));
}
__device__ __forceinline__ void first_stage(const Params& P, uint32_t sb, int n, int bi, int bj) {
  const uint32_t st = sb + RING + ((n + 2) % 3) * 49152, fb = sb + B_FULL1 + 8 * n;
  e_expect(fb, 49152);
  e_tma2d(st, &P.mx, fb, n * 64, bi * 128);
  e_tma3d(st + 16384, &P.mw, fb, 2 * bj * 64, n * 64);
  e_tma3d(st + 32768, &P.mw, fb, (2 * bj + 1) * 64, n * 64);
}

template <bool GF>
__global__ void __launch_bounds__(512, 1) fused_kernel(const __grid_constant__ Params P) {
  extern __shared__ __align__(1024) uint8_t smem_raw[];
  const uint32_t sb = (uint32_t)__cvta_generic_to_shared(smem_raw);
  const unsigned t_start = clk();
  const int tid_all = threadIdx.x, tid = tid_all & 127, lane = tid & 31;
  const int warp = __shfl_sync(~0u, tid_all >> 5, 0), wg = warp >> 2, wi = warp & 3;
  unsigned ep0 = 0;
  if (tid_all == 32) asm volatile("ld.relaxed.gpu.global.u32 %0, [%1];" : "=r"(ep0) : "l"(&g_epoch) : "memory");
  const int L = blockIdx.x, rho = L & 1, cl = L >> 1;
  const int grp = cl >> 2, mem = cl & 3;
  const int bi = 2 * (2 * (grp & 3) + (mem >> 1)) + rho;
  const int bj = 2 * (grp >> 2) + (mem & 1);
  const int rt2 = 2 * (2 * (grp & 7) + (mem >> 1)) + rho;
  const int tt = 2 * (grp >> 3) + (mem & 1);
  const int it2 = L == 0 ? 160 : (bj >= 6 ? 5 * (2 * bi + bj - 6) : -1);

  if (warp == 0) {
    if (lane == 0) { prefetch_map(&P.mx); prefetch_map(&P.mw); mbar_init(sb + B_FULL1, 1); fence_async_smem(); }
    __syncwarp();
    first_stage(P, sb, 0, bi, bj);
    if (lane == 0) {
      TS(30);
      if (sb & 1023) __trap();
      sts32(sb + WMV, 0);
#pragma unroll
      for (int i = 1; i < 43; i++) mbar_init(sb + MISC + 8 * i, (i >= 4 && i < 8) ? 2 + 2 * MC : i == 33 ? 1 + MC : 1);
      asm volatile("fence.mbarrier_init.release.cluster;" ::: "memory");
      fence_async_smem();
    }
  }
  __syncthreads();
  if (MC) asm volatile("barrier.cluster.arrive.relaxed.aligned;" ::: "memory");

  if (warp == 0) {
      wait_until(t_start + T_S1);
      first_stage(P, sb, 1, bi, bj); first_stage(P, sb, 2, bi, bj);
      if (lane < 2) prefetch_l2(g_tab + (L + 128 * lane) * 32);
      if (lane == 0) TS(31);
      bar_arrive(15, 416);
    } else if (wg >= 2) bar_sync(15, 416);
  if (wg == 0) {
    asm volatile("setmaxnreg.dec.sync.aligned.u32 40;");
    if (MC) asm volatile("barrier.cluster.wait.acquire.aligned;" ::: "memory");
    if (wi == 0) {
      int sl = 2;
#pragma unroll 1
      for (int n = 3; n < 10; n++) {
        const uint32_t st = sb + RING + sl * 49152, fb = sb + B_FULL1 + 8 * (n & 3);
        mbar_wait(sb + B_EMPTY1 + 8 * ((n - 3) & 3), ((n - 3) >> 2) & 1);
        e_expect(fb, 49152);
        e_tma2d(st, &P.mx, fb, n * 64, bi * 128);
        if (MC) e_tma3d_mc(st + 16384 + rho * 16384, &P.mw, fb, (2 * bj + rho) * 64, n * 64);
        else { e_tma3d(st + 16384, &P.mw, fb, 2 * bj * 64, n * 64); e_tma3d(st + 32768, &P.mw, fb, (2 * bj + 1) * 64, n * 64); }
        if (++sl == 3) sl = 0;
        if (n == 3) { e_expect(sb + B_MAT, 25600); e_bulk(sb + MAT, g_tab + TAB_D80, 25600, sb + B_MAT); }
      }
#pragma unroll 1
      for (int u = 0; u < 10; u++) {
        const int n = 10 + u, dep = u < 3 ? n - 3 : n - 4;
        const uint32_t st = sb + RING + (u & 3) * 40960, fb = sb + B_FULL1 + 8 * (n & 3);
        mbar_wait(sb + B_EMPTY1 + 8 * (dep & 3), (dep >> 2) & 1);
        if (u == 3) mbar_wait(sb + B_SPARE, 0);
        e_expect(fb, bj < 6 ? 40960 : 32768);
        e_tma2d(st, &P.mx, fb, u * 64, bi * 128);
        if (!MC) e_tma3d(st + 16384, &P.mw, fb, (16 + bj) * 64, u * 64);
        else if (rho == 0) e_tma3d_mc(st + 16384, &P.mw, fb, (16 + bj) * 64, u * 64);
        if (bj < 6 && (rho || !MC)) {
          if (u == 0) { mbar_wait(sb + B_WC, 0); fence_async_glob(); }
          if (MC) e_tma2d_mc(st + 32768, &P.mcl, fb, 0, (bj * 10 + u) * 64); else e_tma2d(st + 32768, &P.mcl, fb, 0, (bj * 10 + u) * 64);
        }
      }
      if (lane == 0) TS(0);
      mbar_wait(sb + B_FA, 0);
      fence_async_glob();
      if (lane == 0) TS(1);
      const uint8_t* srcA = g_h + (size_t)rt2 * 27 * 8192;
      const uint8_t* srcB = g_wd + (size_t)tt * 27 * 20480;
      sl = 3;
      int ph = 1, bs = 0;
#pragma unroll 1
      for (int m = 0; m < 27; m++) {
        const uint32_t st = sb + RING + sl * 28672, fb = sb + B_FULL2 + 8 * bs;
        if (m < 6) mbar_wait(sb + B_EMPTY1 + 8 * ((0x332110 >> (4 * m)) & 3), 0);
        else mbar_wait(sb + B_EMPTY2 + 8 * bs, ph);
        e_expect(fb, 28672);
        e_bulk(st + 8192, srcB, 20480, fb);
        if (m == 16) { if (lane == 0) TS(2); mbar_wait(sb + B_FB, 0); fence_async_glob(); if (lane == 0) TS(3); }
        e_bulk(st, srcA, 8192, fb);
        srcA += 8192; srcB += 20480;
        if (++sl == 6) sl = 0;
        if (++bs == 6) { bs = 0; ph ^= 1; }
      }
      mbar_wait(sb + B_XFREE, 0);
      e_expect(sb + B_XFULL, 20480);
#pragma unroll 1
      for (int p = 0; p < 5; p++) e_tma2d(sb + RING + p * 4096, &P.mxf, sb + B_XFULL, 128 * p + 32 * tt, rt2 * 64);
    } else {
      if (tid_all == 32) { sts32(sb + EPOCHV, ep0 + 1); mbar_arrive(sb + B_EPOCH); }
      mbar_wait(sb + B_EPOCH, 0);
      const unsigned ep1 = lds32(sb + EPOCHV);
      if (wi == 1) {
        bar_sync(13, 160);
        uint32_t rb = 0;
#pragma unroll
        for (int k = 0; k < 5; k++) rb |= readback(g_z + (bi * 8 + bj) * 5120 + (lane + 32 * k) * 32);
        settle(rb);
        e_publish(FL_Z);
        if (lane == 0) TS(14);
        const int it1 = L + (L >> 2) + 1;
        poll(FL_Z, ep1 * 128); acquire();
        z_fetch(P, sb, it1);
        if (lane == 0) TS(15);
        bar_sync(14, 160);
#pragma unroll
        for (int k = 0; k < 11; k++) rb |= readback(g_cw + min(lane + 32 * k, 321) * 2048 + (L >> 3) * 128 + (L & 7) * 16);
        settle(rb);
        if (lane == 0) post_max(FL_W, ep1, lds32(sb + WMV));
        const unsigned wmax = poll_max(FL_W, ep1);
        acquire();
        if (lane == 0) { sts32(sb + FEV, min(wmax >> 7, 247u)); mbar_arrive(sb + B_WRDY); TS(13); }
#pragma unroll 1
        for (int r = 0; r < (it2 >= 0 ? 2 : 1); r++) {
          const int ka = r ? it2 : it1, kb = ka ? 320 - ka : 0, ja = ka / 5, jb = kb / 5;
          bar_sync(11, 160);
          if (ka != 160) e_tma4d_st(&P.my, sb + E1, 2 * ja, ka - 5 * ja);
          if (ka != 0) e_tma4d_st(&P.my, sb + E1 + 8192, 2 * jb, kb - 5 * jb);
          bulk_commit(); bulk_wait();
          e_arrive(sb + ((r == 0 && it2 >= 0) ? B_YFREE : B_SFREE));
          const uint8_t *pa = g_y + lane * 81920 + (ka - 5 * ja) * 16384 + ja * 256, *pb = g_y + lane * 81920 + (kb - 5 * jb) * 16384 + jb * 256;
          settle(readback(pa) | readback(pa + 128) | readback(pb) | readback(pb + 128));
          e_publish(r ? FL_Y2 : FL_Y);
          if (lane == 0) TS(18 + r);
        }
      } else if (wi == 2) {
        wait_until(t_start + T_PA);
        if (bi < 14) e_pf3d(&P.mw, (2 * bj + (bi & 1)) * 64, (3 + (bi >> 1)) * 64);
        wait_until(t_start + T_PB);
        if (bi >= 6 && bj < 6 && !(bj & 1)) e_pf3d(&P.mw, (24 + (bj >> 1)) * 64, (bi - 6) * 64);
#pragma unroll 1
        for (int i = lane * 128; i < 17280; i += 4096) prefetch_l2((const uint8_t*)P.wd + L * 17280 + i);
        wait_until(t_start + T_PF1);
        if (bi < 10) e_pf3d(&P.mw, (16 + bj) * 64, bi * 64);
        wait_until(t_start + T_PF2);
#pragma unroll 1
        for (int i = lane * 128; i < 10272; i += 4096) { prefetch_l2((const uint8_t*)P.wr + L * 10272 + i); prefetch_l2((const uint8_t*)P.wi + L * 10272 + i); }
        if ((SKIP & 2) && L < 60) e_publish(FL_WC);
        if (L < 60 && !(SKIP & 2)) {
          wait_until(t_start + T_WC);
          e_expect(sb + B_WDT, 8192);
          e_tma3d(sb + WSTG, &P.mwh, sb + B_WDT, 24 * 64 + (L / 10) * 32, (L % 10) * 64);
          mbar_wait(sb + B_WDT, 0);
          e_tma4d_st3(&P.mcs, sb + WSTG, L);
          bulk_commit(); bulk_wait();
          settle(readback(g_wc + L * 8192 + lane * 128) | readback(g_wc + L * 8192 + lane * 128 + 64) | readback(g_wc + L * 8192 + 4096 + lane * 128) | readback(g_wc + L * 8192 + 4096 + lane * 128 + 64));
          e_publish(FL_WC);
        }
        if (L < 108) {
          wait_until(t_start + T_WD);
          e_expect(sb + B_WDT, 20480);
          e_tma5d(sb + WSTG, &P.mwd, sb + B_WDT, 32 * ((2 * L) / 54), 4 * ((2 * L) % 54));
          wait_until(t_start + T_WD + 700);
          e_tma5d(sb + WSTG + 10240, &P.mwd, sb + B_WDT, 32 * ((2 * L + 1) / 54), 4 * ((2 * L + 1) % 54));
          mbar_wait(sb + B_WDT, L < 60);
#pragma unroll 1
          for (int k = 0; k < 20; k++) {
            e_bulk_st(g_wd + (size_t)L * 20480 + k * 1024, sb + WSTG + k * 1024, 1024);
            if (k == 15) { bulk_commit(); bulk_wait(); release2(sb + B_SPARE, lane); }
            wait_until(clk() + T_WDS);
          }
          bulk_commit(); bulk_wait();
        } else release2(sb + B_SPARE, lane);
        uint32_t rb = 0;
        if (L < 108) {
#pragma unroll
          for (int k = 0; k < 5; k++) rb |= readback(g_wd + (size_t)L * 20480 + (lane + 32 * k) * 128);
          settle(rb);
          e_publish(FL_WD);
        }
        if (lane == 0) TS(6);
        bar_sync(2, 288);
        rb = 0;
#pragma unroll
        for (int k = 0; k < 8; k++) rb |= readback(g_h + (size_t)(2 * bi + (k & 1)) * 27 * 8192 + 2 * bj * 8192 + (k >> 1) * 4096 + lane * 128);
        settle(rb);
        e_publish(FL_HA + 2 * bi); e_publish(FL_HA + 2 * bi + 1);
        if (lane == 0) TS(7);
        poll(FL_WD, ep1 * 108); poll(FL_HA + rt2, ep1 * 8); acquire();
        e_arrive(sb + B_FA);
        const unsigned t = poll_max(FL_T2, ep1);
        if (lane == 0) { sts32(sb + TGV, t_start + t + T_G2); mbar_arrive(sb + B_TG); }
        const uint8_t* srcY = g_y + (size_t)rt2 * 5 * 16384;
        mbar_wait(sb + B_SFREE, 0);
        poll(FL_Y, ep1 * 128); acquire();
        if (lane == 0) TS(28);
#pragma unroll 1
        for (int k = 0; k < 3; k++) { e_expect(sb + B_P4 + 8 * k, 16384); e_bulk(sb + SIDE + k * 16384, srcY + (1 + k) * 16384, 16384, sb + B_P4 + 8 * k); }
        mbar_wait(sb + B_P4F, 0);
        e_expect(sb + B_P4, 16384); e_bulk(sb + SIDE, srcY + 4 * 16384, 16384, sb + B_P4);
        poll(FL_Y2, ep1 * 33); acquire();
        e_expect(sb + B_P4 + 8, 16384); e_bulk(sb + SIDE + 16384, srcY, 16384, sb + B_P4 + 8);
        if (lane == 0) { TS(27); if (L == 0) asm volatile("st.relaxed.gpu.global.u32 [%0], %1;" ::"l"(&g_epoch), "r"(ep1) : "memory"); }
      } else {
        wait_until(t_start + T_WC + T_WCP);
        if (bj < 6 && (rho || !MC)) poll(FL_WC, ep1 * 60);
        acquire();
        e_arrive(sb + B_WC);
        if (lane == 0) TS(37);
        wait_until(t_start + T_R0);
        { const unsigned t = poll_max(FL_T1, ep1); if (lane == 0) { sts32(sb + TBV, t_start + t + T_TILEB); mbar_arrive(sb + B_TB); } }
        wait_until(t_start + T_CS);
#pragma unroll 1
        for (int k = 0; k < 3; k++) {
          const uint2* pc = g_cs + (k < 2 ? k * F_ + 64 * (16 + bj) : 24 * 64 + 32 * min(bj, 5)) + lane;
          const int o2 = k < 2 ? 32 : F_;
          float c[2];
          for (int spin = 0;; spin++) {
            uint32_t bad = 0;
#pragma unroll
            for (int h = 0; h < 2; h++) {
              const uint2* q = pc + h * o2;
              const uint2 a0 = ld_tag(q), a1 = ld_tag(q + 2 * F_), a2 = ld_tag(q + 4 * F_), a3 = ld_tag(q + 6 * F_), a4 = ld_tag(q + 8 * F_);
              c[h] = (__uint_as_float(a0.x) + __uint_as_float(a1.x)) + (__uint_as_float(a2.x) + __uint_as_float(a3.x)) + __uint_as_float(a4.x);
              bad |= (a0.y ^ ep1) | (a1.y ^ ep1) | (a2.y ^ ep1) | (a3.y ^ ep1) | (a4.y ^ ep1);
            }
            if (!__any_sync(~0u, bad)) break;
            if (spin > 1000000) __trap();
            __nanosleep(300);
          }
#pragma unroll
          for (int h = 0; h < 2; h++) {
            const float hi = bf_round(c[h]), mid = bf_round(c[h] - hi), lo = bf_round(c[h] - hi - mid);
            sts128(sb + BEXT + (256 + k * 64 + h * 32 + lane) * 16, pack_bf16(hi, mid), pack_bf16(lo, 0.f), 0, 0);
          }
        }
        fence_async_smem();
        __syncwarp();
        e_arrive(sb + B_PAR2);
        if (lane == 0) TS(4);
        bar_sync(3, 288);
        uint32_t rb = 0;
#pragma unroll
        for (int k = 0; k < 6; k++)
          rb |= readback(g_h + (size_t)(2 * bi + (k & 1)) * 27 * 8192 + (k < 4 ? (16 + bj) * 8192 + (k >> 1) * 4096 : 24 * 8192 + min(bj, 5) * 4096) + lane * 128);
        settle(rb);
        e_publish(FL_HB + 2 * bi); e_publish(FL_HB + 2 * bi + 1);
        if (lane == 0) TS(8);
        poll(FL_HB + rt2, ep1 * 8); acquire();
        e_arrive(sb + B_FB);
      }
    }
  } else if (wg == 1) {
    const int l8 = lane & 7, mrow = 4 * wi + (lane >> 3), row = 2 * (mrow & 7) + (mrow >> 3);
    uint2 raw[5][4];
    {
      const __nv_bfloat16* xrow = P.x + (size_t)(bi * 128 + bj * 16 + row) * D_ + 4 * l8;
      wait_until(t_start + T_X);
#pragma unroll
      for (int t = 0; t < 5; t++)
#pragma unroll
        for (int p = 0; p < 4; p++) raw[t][p] = __ldg((const uint2*)(xrow + 32 * t + 160 * p));
    }
    uint32_t r4[32];
#pragma unroll
    for (int i = 0; i < 8; i++) { const uint4 v = __ldg((const uint4*)(g_tab + TAB_R4) + 8 * i + l8); r4[4 * i] = v.x; r4[4 * i + 1] = v.y; r4[4 * i + 2] = v.z; r4[4 * i + 3] = v.w; }
    bar_sync(15, 416);
    asm volatile("setmaxnreg.inc.sync.aligned.u32 136;");
    if (MC) asm volatile("barrier.cluster.wait.acquire.aligned;" ::: "memory");
    mbar_wait(sb + B_EPOCH, 0);
    const unsigned ep1 = lds32(sb + EPOCHV);
    uint4 cv[10];
    {
      if (tid == 32) TS(10);
      wait_until(t_start + T_P1);
      float z[5][4][4];
      float sm[4] = {0.f, 0.f, 0.f, 0.f}, sqq[4] = {0.f, 0.f, 0.f, 0.f};
#pragma unroll
      for (int t = 0; t < 5; t++)
#pragma unroll
        for (int p = 0; p < 4; p++) {
          z[t][p][0] = bf_lo(raw[t][p].x); z[t][p][1] = bf_hi(raw[t][p].x); z[t][p][2] = bf_lo(raw[t][p].y); z[t][p][3] = bf_hi(raw[t][p].y);
          sm[p] += (z[t][p][0] + z[t][p][1]) + (z[t][p][2] + z[t][p][3]);
          sqq[p] = fmaf(z[t][p][0], z[t][p][0], fmaf(z[t][p][1], z[t][p][1], fmaf(z[t][p][2], z[t][p][2], fmaf(z[t][p][3], z[t][p][3], sqq[p]))));
        }
      float sum = (sm[0] + sm[1]) + (sm[2] + sm[3]), sq = (sqq[0] + sqq[1]) + (sqq[2] + sqq[3]);
      if (tid == 0) TS(34);
#pragma unroll
      for (int o = 1; o < 8; o <<= 1) { sum += __shfl_xor_sync(~0u, sum, o); sq += __shfl_xor_sync(~0u, sq, o); }
      const float mean = sum * (1.f / 640.f), var = fmaxf(fmaf(-mean, mean, sq * (1.f / 640.f)), 0.f);
      float sd, rinv;
      asm("sqrt.approx.f32 %0, %1;" : "=f"(sd) : "f"(bf_round(bf_round(var) + 1e-5f)));
      asm("rcp.approx.f32 %0, %1;" : "=f"(rinv) : "f"(bf_round(sd)));
      const float mb = bf_round(mean), off = -mb * rinv;
      if (l8 == 0) st_tag(&g_stat[bi * 128 + bj * 16 + row], __float_as_uint(mb) | (ep1 & 0xffff), __float_as_uint(rinv));
      const uint32_t va = sb + VT + mrow * 32 + ((l8 * 4) ^ ((mrow & 4) << 2));
      C2 y[5][4];
#pragma unroll
      for (int t = 0; t < 5; t++)
#pragma unroll
        for (int p = 0; p < 4; p++) {
          y[t][p] = {u2h(pack_f16(fmaf(z[t][p][0], rinv, off), fmaf(z[t][p][2], rinv, off))), u2h(pack_f16(fmaf(z[t][p][1], rinv, off), fmaf(z[t][p][3], rinv, off)))};
          asm volatile("" : "+r"(*(uint32_t*)&y[t][p].x), "+r"(*(uint32_t*)&y[t][p].y));
        }
      cs_load(cv, (L & 4 ? P.w1 : P.w0) + (size_t)(L & 3) * 160 * F_ + (L >> 3) * 64, tid);
#pragma unroll
      for (int t = 0; t < 5; t++) {
        dft4(y[t][0], y[t][1], y[t][2], y[t][3]);
#pragma unroll
        for (int q = 0; q < 4; q++) {
          if (q) y[t][q] = cmulh(y[t][q], u2h(r4[6 * t + 2 * q - 2]), u2h(r4[6 * t + 2 * q - 1]));
          sts32(va + t * 2048 + q * 512, h2u(y[t][q].x)); sts32(va + t * 2048 + q * 512 + 10240, h2u(y[t][q].y));
        }
      }
      if (tid == 0) TS(11);
    }
    fence_async_smem();
    cs_finish(cv, g_cs + ((L & 3) * 2 + ((L >> 2) & 1)) * F_ + (L >> 3) * 64, sb, ep1, tid);
    if (tid == 0) TS(39);
    mbar_wait(sb + B_MAT, 0);
    wait_until(t_start + T_P2);
    float acc[80];
    {
      constexpr uint64_t HA = desc_hi(16, 256, 3), HB = desc_hi(1280, 128, 0);
      wg_fence();
      const uint64_t are = desc(HA, sb + VT), bc = desc(HB, sb + MAT);
#pragma unroll
      for (int ks = 0; ks < 5; ks++) {
        mma_h80<0>(acc, are + 128 * ks, bc + 160 * ks, ks);
        mma_h80<0>(acc, are + 128 * ks + 640, bc + 160 * ks + 800, 1);
      }
#pragma unroll
      for (int ks = 0; ks < 5; ks++) {
        mma_h80<40>(acc, are + 128 * ks + 640, bc + 160 * ks, ks);
        mma_h80_neg<40>(acc, are + 128 * ks, bc + 160 * ks + 800, 1);
      }
      wg_commit();
    }
    wg_wait<0>();
    if (tid == 0) mbar_arrive(sb + B_P2D);
    bar_sync(1, 128);
    {
      const int r8 = L & 7, ab = wi >> 1, sa = 4 * ((L >> 3) & 3) + 64 * (L >> 5);
      const uint8_t* src = (const uint8_t*)((wi & 1) ? P.wi : P.wr) + (ab ? 640 * ((8 - r8) & 7) + 320 : 640 * r8) + lane * 16;
      const int s0 = ab ? (r8 ? 255 : 256) - sa : sa, ds = ab ? -1 : 1;
      if (lane < 21) {
#pragma unroll
        for (int k = 0; k < 16; k++)
          asm volatile("cp.async.cg.shared.global [%0], [%1], 16;" ::"r"(sb + MAT + wi * 5632 + k * 352 + ((k >> 2) & 1) * 16 + lane * 16),
                       "l"(src + ((s0 + ds * ((k & 3) + 16 * (k >> 2))) & 255) * 5136) : "memory");
      }
    }
    if (tid == 0) TS(41);
    {
      uint2* zp = (uint2*)(g_z + (bi * 8 + bj) * 5120 + wi * 1280) + (lane & 3) * 8 + (lane >> 2);
#pragma unroll
      for (int i = 0; i < 20; i++) {
        const int al = i >> 1, e = i & 1;
        zp[i * 32] = make_uint2(pack_f16(acc[4 * al + e], acc[40 + 4 * al + e]), pack_f16(acc[4 * al + 2 + e], acc[42 + 4 * al + e]));
      }
    }
    bar_arrive(13, 160);
    if (tid == 0) TS(12);
    __half2 tw1[16], tw2[16];
    {
      const int r8 = L & 7, rm = (8 - r8) & 7, u = lane & 3;
      uint32_t* dst = g_cw + (L >> 3) * 128 + r8 * 16;
      uint32_t wm = 0;
      twiddle_load(tw1, g_tab + TAB_TW1 + 4 * tid, 128);
      twiddle_load(tw2, g_tab + TAB_TW2 + 4 * (tid >> 4), 8);
      if (wi == 3) {
        const int ab = lane >> 4, mu = r8 + 32 * ((L >> 3) & 3) + 8 * ((lane >> 2) & 3) + 128 * (4 * (L >> 5) + u);
        const int o1 = mu * DF_ + 320 * ab, o2 = ((2048 - mu) & 2047) * DF_ + 320 * ab;
        const float r1 = __bfloat162float(P.wr[o1]), i1 = __bfloat162float(P.wi[o1]), r2 = __bfloat162float(P.wr[o2]), i2 = __bfloat162float(P.wi[o2]);
        const uint32_t v = pack_bf16(0.5f * (r1 + r2), ab ? 0.5f * (i2 - i1) : 0.5f * (i1 - i2));
        dst[ab * 2048 + (lane & 15)] = v;
        wm = max(v & 0x7fffu, (v >> 16) & 0x7fffu);
      }
      const int jj = lane & 1, jb = ((lane >> 2) & 2) | jj, ib = (lane >> 1) & 3;
      const uint32_t aA = sb + MAT + (lane >> 4) * 5632 + jb * 1408 + ib * 352 + jj * 16, aB = aA + 11264;
      asm volatile("cp.async.wait_all;" ::: "memory");
      bar_sync(1, 128);
      if (tid == 0) TS(33);
      uint32_t mu = 0, ms = 0;
#pragma unroll
      for (int ab = 0; ab < 2; ab++) {
        uint4 m[6];
        const uint32_t am = (ab ? aB : aA) + 16 * wi;
#pragma unroll
        for (int k = 0; k < 6; k++) m[k] = ldsm4t(am + (k < 5 ? 64 * k : (wi == 0 ? 320 : 0)));
        const int it0 = ab ? 160 + rm - 8 * wi - (lane >> 2) : 8 * wi - r8 + (lane >> 2), stp = ab ? -32 : 32;
        uint32_t* d = dst + (2 * it0 + ab) * 2048 + u * 4;
#pragma unroll
        for (int k = 0; k < 6; k++) {
          const bool ok = (k >= 1 && k <= 4) || (unsigned)(it0 + k * stp - 1) < 160u;
          if (ok) {
            mu = __vmaxu2(__vmaxu2(__vmaxu2(mu, m[k].x), m[k].y), __vmaxu2(m[k].z, m[k].w));
            ms = __vmaxs2(__vmaxs2(__vmaxs2(ms, m[k].x), m[k].y), __vmaxs2(m[k].z, m[k].w));
            stg128(d + k * stp * 4096, __byte_perm(m[k].x, m[k].z, 0x5410), __byte_perm(m[k].x, m[k].z, 0x7632), __byte_perm(m[k].y, m[k].w, 0x5410), __byte_perm(m[k].y, m[k].w, 0x7632));
          }
        }
      }
      mu = __vmaxu2(mu & 0x7fff7fffu, ms);
      wm = __reduce_max_sync(~0u, max(wm, max(mu & 0xffffu, mu >> 16)));
      if (lane == 0) asm volatile("red.shared.max.u32 [%0], %1;" ::"r"(sb + WMV), "r"(wm) : "memory");
      bar_arrive(14, 160);
      if (tid == 0) TS(35);
    }
    if (L < 110) {
      uint4 cw8[8];
      cs_load(cw8, ((L / 5) & 1 ? P.w1 : P.w0) + (size_t)(L % 5) * 128 * F_ + (16 + L / 10) * 64, tid);
      cs_finish(cw8, g_cs + ((L % 5) * 2 + ((L / 5) & 1)) * F_ + (16 + L / 10) * 64, sb, ep1, tid);
    }
    if (tid == 0) TS(38);
    const uint32_t e1r = sb + E1 + ((tid & 15) * 128 + ((tid >> 4) ^ (tid & 15))) * 8, e2w = sb + E2 + ((tid >> 4) * 256 + (tid & 15)) * 8;
#pragma unroll 1
    for (int r = 0; r < (it2 >= 0 ? 2 : 1); r++) {
      const int item = r ? it2 : L + (L >> 2) + 1;
      C2 v[16];
      mbar_wait(sb + B_ZIN, r);
#pragma unroll
      for (int a = 0; a < 16; a++) {
        const uint32_t za = lds32(sb + ZIN + (tid + 128 * a) * 4), zb = lds32(sb + ZIN + 8192 + (tid + 128 * a) * 4);
        v[a] = {u2h(__byte_perm(za, zb, 0x5410)), u2h(__byte_perm(za, zb, 0x7632) ^ 0x80000000u)};
      }
      if (r) mbar_wait(sb + B_YFREE, 0);
      fence_async_smem();
      bar_sync(1, 128);
      if (wi == 0 && r == 0 && it2 >= 0) z_fetch(P, sb, it2);
      if (tid == 0) TS(40);
#pragma unroll 1
      for (int pass = 0; pass < 4; pass++) {
        uint4 wa[4], wb[4];
        if (pass == 1) {
          mbar_wait(sb + B_WRDY, 0);
          const uint4* cw = (const uint4*)g_cw + (size_t)item * 1024 + wi * 32 + (lane & 7) * 4 + (lane >> 3);
#pragma unroll
          for (int a = 0; a < 4; a++) { wa[a] = ldcg128(cw + 128 * a); wb[a] = ldcg128(cw + 512 + 128 * a); }
        }
        dft16(v);
        if (!(pass & 1)) {
          twiddle_store<1024, 8>(v, tw1, sb + E1 + tid * 8);
          bar_sync(1, 128);
#pragma unroll
          for (int b = 0; b < 16; b++) { const uint2 t = lds64((e1r ^ ((b & 1) * 64)) + (b >> 1) * 128); v[b] = {u2h(t.x), u2h(t.y)}; }
          continue;
        }
        twiddle_store<128, 0>(v, tw2, e2w);
        bar_sync(1, 128);
        C2 u[16];
#pragma unroll
        for (int i = 0; i < 16; i++) { const uint2 t = lds64(sb + E2 + tid * 8 + ((i & 7) * 256 + (i >> 3) * 128) * 8); u[i] = {u2h(t.x), u2h(t.y)}; }
        dft8<0>(u); dft8<8>(u);
#pragma unroll
        for (int a = 0; a < 16; a++) v[a] = u[8 * (a & 1) + 4 * ((a >> 1) & 1) + (a >> 2)];
        if (pass == 1) {
          if (tid == 0) TS(42);
          const float2 ph = cispi(item * (1.f / 320.f));
          const uint32_t sc = ((248 - lds32(sb + FEV)) << 7) * 0x10001u;
          const __half2 km = __float2half2_rn(1.f - ph.y), kp = __float2half2_rn(1.f + ph.y), kc = __float2half2_rn(ph.x);
#pragma unroll
          for (int a = 0; a < 16; a++) {
            const uint4 A4 = wa[a >> 2], B4 = wb[a >> 2];
            const uint32_t sa = hmul2_bf((a & 3) == 0 ? A4.x : (a & 3) == 1 ? A4.y : (a & 3) == 2 ? A4.z : A4.w, sc);
            const uint32_t sb2 = hmul2_bf((a & 3) == 0 ? B4.x : (a & 3) == 1 ? B4.y : (a & 3) == 2 ? B4.z : B4.w, sc ^ 0x80000000u);
            const __half2 p = u2h(pack_f16(bf_lo(sa), bf_lo(sb2))), q2 = u2h(pack_f16(bf_hi(sa), bf_hi(sb2)));
            const __half2 ps = __lowhigh2highlow(p), qs = __lowhigh2highlow(q2);
            const __half2 c1r = __hfma2(p, km, __hmul2(ps, kp)), c1i = __hfma2(q2, km, __hmul2(qs, kp));
            const __half2 c2r = __hmul2(__hsub2(qs, q2), kc), c2i = __hmul2(__hsub2(p, ps), kc);
            const __half2 R = v[a].x, I = v[a].y, Rs = __lowhigh2highlow(R), Is = __lowhigh2highlow(I);
            v[a].x = __hfma2(c1r, R, __hfma2(__hneg2(c1i), I, __hfma2(c2r, Rs, __hneg2(__hmul2(c2i, Is)))));
            v[a].y = __hfma2(__hneg2(c1r), I, __hfma2(__hneg2(c1i), R, __hfma2(__hneg2(c2r), Is, __hneg2(__hmul2(c2i, Rs)))));
          }
          if (tid == 0) TS(43);
        }
      }
      if (tid == 0) TS(44);
      const int kb = item ? 320 - item : 0, ja = item / 5, jb = kb / 5, sp = tid & 63;
      const uint32_t y0 = sb + E1 + (tid >> 6) * 256 + (sp & 7) * 2;
      const uint32_t ya = y0 + (((sp >> 3) ^ ((2 * ja) & 7)) << 4), yb = y0 + 8192 + (((sp >> 3) ^ ((2 * jb) & 7)) << 4);
#pragma unroll
      for (int a = 0; a < 16; a++) {
        sts16(ya + a * 512, h2u(v[a].x));
        sts16((ya ^ 16) + a * 512 + 128, h2u(v[a].y));
        sts16(yb + a * 512, h2u(v[a].x) >> 16);
        sts16((yb ^ 16) + a * 512 + 128, h2u(v[a].y) >> 16);
      }
      fence_async_smem();
      bar_arrive(11, 160);
      if (tid == 0) TS(16 + r);
    }
  } else {
    asm volatile("setmaxnreg.inc.sync.aligned.u32 168;");
    if (MC) asm volatile("barrier.cluster.wait.acquire.aligned;" ::: "memory");
    const int w = wg - 2, g = lane >> 2, lam = lane & 3;
    constexpr uint64_t HA = desc_hi(16, 1024, 1), HH = desc_hi(128, 512, 0), HB1 = desc_hi(8192, 1024, 1), HB2 = desc_hi(2048, 512, 2), HBE = desc_hi(0, 128, 0);
    float acc[128];
    uint32_t pk[48];
    const int ct = tid_all - 256;
    uint64_t q0, q1, q2, q3, q4, q5;
#define PARAM_PTRS const uint2 *pc0 = g_cs + ((ct >> 6) & 1) * F_ + 64 * (2 * bj + (ct >> 7)) + (ct & 63), *pst = g_stat + bi * 128 + 64 * w + 16 * wi + g;
#define LD_PARAMS asm volatile("ld.relaxed.gpu.global.b64 %0, [%6];\nld.relaxed.gpu.global.b64 %1, [%6+27648];\nld.relaxed.gpu.global.b64 %2, [%6+55296];\n"  \
      "ld.relaxed.gpu.global.b64 %3, [%6+82944];\nld.relaxed.gpu.global.b64 %4, [%7];\nld.relaxed.gpu.global.b64 %5, [%7+64];"                              \
      : "=l"(q0), "=l"(q1), "=l"(q2), "=l"(q3), "=l"(q4), "=l"(q5) : "l"(pc0), "l"(pst) : "memory");
#define LO(q) ((uint32_t)(q))
#define HI(q) ((uint32_t)((q) >> 32))
    {
#define TA_STEP(N, SL, MID)                                                                                 \
      {                                                                                                \
        mbar_wait(sb + B_FULL1 + 8 * ((N) & 3), ((N) >> 2) & 1);                                       \
        TA_TS(N)                                                                                       \
        const uint32_t st = sb + RING + (SL) * 49152;                                                  \
        const uint64_t da = desc(HA, st + w * 8192), db = desc(HB1, st + 16384);                       \
        wg_fence();                                                                                    \
        _Pragma("unroll") for (int k = 0; k < 4; k++) { mma_n128<0>(acc, da + 2 * k, db + 128 * k, (N) | k); mma_n128<64>(acc, da + 2 * k, db + 1024 + 128 * k, (N) | k); } \
        wg_commit();                                                                                   \
        MID                                                                                            \
        if ((N) > 0) { wg_wait<1>(); release2(sb + B_EMPTY1 + 8 * (((N) - 1) & 3), tid); }              \
      }
#define TA_TS(N) if ((N) == 0 && tid_all == 256) TS(20);
      int sl = 2;
#pragma unroll 1
      for (int n = 0; n < 8; n++) {
        if (n == N_P2) mbar_wait(sb + B_P2D, 0);
        TA_STEP(n, sl, )
        if (n == 5) { mbar_wait(sb + B_EPOCH, 0); if (tid_all == 256) post_max(FL_T1, lds32(sb + EPOCHV), clk() - t_start); }
        if (++sl == 3) sl = 0;
      }
      PARAM_PTRS
      TA_STEP(8, 1, LD_PARAMS)
    }
    if (tid_all == 256) TS(21);
    mbar_wait(sb + B_EPOCH, 0);
    const unsigned e = lds32(sb + EPOCHV);
    if (__any_sync(~0u, (HI(q0) ^ e) | (HI(q1) ^ e) | (HI(q2) ^ e) | (HI(q3) ^ e) | (((LO(q4) ^ e) | (LO(q5) ^ e)) & 0xffff))) {
      PARAM_PTRS
      asm volatile("{\n.reg .pred p;\n.reg .u32 c, a, b, d;\nmov.u32 c, 0;\nLW:\n"
        "ld.relaxed.gpu.global.u32 a, [%0+4];\nld.relaxed.gpu.global.u32 b, [%0+27652];\nxor.b32 a, a, %2;\nxor.b32 b, b, %2;\nor.b32 d, a, b;\n"
        "ld.relaxed.gpu.global.u32 a, [%0+55300];\nld.relaxed.gpu.global.u32 b, [%0+82948];\nxor.b32 a, a, %2;\nxor.b32 b, b, %2;\nor.b32 d, d, a;\nor.b32 d, d, b;\n"
        "ld.relaxed.gpu.global.u32 a, [%1];\nld.relaxed.gpu.global.u32 b, [%1+64];\nxor.b32 a, a, %2;\nxor.b32 b, b, %2;\nor.b32 a, a, b;\nand.b32 a, a, 0xffff;\nor.b32 d, d, a;\n"
        "setp.eq.u32 p, d, 0;\nvote.sync.all.pred p, p, 0xffffffff;\n@p bra LD;\nadd.u32 c, c, 1;\nsetp.lt.u32 p, c, 1000000;\n@p bra LW;\ntrap;\nLD:\n}" ::"l"(pc0), "l"(pst), "r"(e) : "memory");
      LD_PARAMS
    }
    {
      const float c = (__uint_as_float(LO(q0)) + __uint_as_float(LO(q1))) + (__uint_as_float(LO(q2)) + __uint_as_float(LO(q3)));
      const float hi = bf_round(c), mid = bf_round(c - hi), lo = bf_round(c - hi - mid);
      sts128(sb + BEXT + ct * 16, pack_bf16(hi, mid), pack_bf16(lo, 0.f), 0, 0);
    }
    fence_async_smem();
    bar_sync(6, 256);
    if (tid_all == 256) TS(36);
    const uint32_t mm = __byte_perm(LO(q4), LO(q5), 0x7632) ^ 0x80008000u;
    const uint32_t ea0 = __byte_perm(mm, 0, lam == 0 ? 0x1010 : (lam == 1 ? 0x4410 : 0x4444)), ea1 = __byte_perm(mm, 0, lam == 0 ? 0x3232 : (lam == 1 ? 0x4432 : 0x4444));
    const float hr0 = 0.5f * __uint_as_float(HI(q4)), hr1 = 0.5f * __uint_as_float(HI(q5));
    uint8_t* hrow = g_h + (size_t)(2 * bi + w) * 27 * 8192 + wi * 1024 + lam * 128 + g * 16;
    constexpr int c1 = 4096;
    constexpr int G0 = GF ? 0 : 8, U0 = GF ? 8 : 0;
    uint4 h0, h1, h2, h3;
    {
      mbar_wait(sb + B_FULL1 + 8 * (9 & 3), (9 >> 2) & 1);
      const uint32_t st = sb + RING + 2 * 49152;
      const uint64_t da = desc(HA, st + w * 8192), db = desc(HB1, st + 16384);
      wg_fence();
#pragma unroll
      for (int k = 0; k < 4; k++) mma_n128<0>(acc, da + 2 * k, db + 128 * k, 1);
      mma_n128_ext<0>(acc, ea0, ea1, desc(HBE, sb + BEXT));
      wg_commit();
#pragma unroll
      for (int k = 0; k < 4; k++) mma_n128<64>(acc, da + 2 * k, db + 1024 + 128 * k, 1);
      mma_n128_ext<64>(acc, ea0, ea1, desc(HBE, sb + BEXT + 128 * 16));
      wg_commit();
      wg_wait<2>();
      release2(sb + B_EMPTY1 + 8 * (8 & 3), tid);
      wg_wait<1>();
      h0 = h_unit_acc<G0, U0, 0>(acc, hr0); h1 = h_unit_acc<G0, U0, 1>(acc, hr1);
      h2 = h_unit_acc<G0 + 4, U0 + 4, 0>(acc, hr0); h3 = h_unit_acc<G0 + 4, U0 + 4, 1>(acc, hr1);
      wg_wait<0>();
      release2(sb + B_EMPTY1 + 8 * (9 & 3), tid);
    }
#pragma unroll
    for (int i = 0; i < 32; i++) pk[i] = pack_bf16(acc[64 + 2 * i], acc[65 + 2 * i]);
    if (tid_all == 256) TS(22);
    mbar_wait(sb + B_TB, 0);
    wait_until(lds32(sb + TBV));
    if (tid_all == 256) TS(46);
    float accB[96];
#define TB_STEP(U, FIRST)                                                                                 \
    {                                                                                                  \
      mbar_wait(sb + B_FULL1 + 8 * ((10 + (U)) & 3), ((10 + (U)) >> 2) & 1);                           \
      const uint32_t st = sb + RING + ((U) & 3) * 40960;                                               \
      const uint64_t da = desc(HA, st + w * 8192), db = desc(HB1, st + 16384);                         \
      wg_fence();                                                                                      \
      if (FIRST) mma_n192_first<0>(accB, da, db); else mma_n192(accB, da, db, 1);                      \
      mma_n192(accB, da + 2, db + 128, 1); mma_n192(accB, da + 4, db + 256, 1); mma_n192(accB, da + 6, db + 384, 1); \
      wg_commit();                                                                                     \
    }
#define TB_REL(U) { wg_wait<1>(); release2(sb + B_EMPTY1 + 8 * ((9 + (U)) & 3), tid); }
    {
      uint8_t* hp = hrow + 2 * bj * 8192;
      TB_STEP(0, true);
      h_store(hp, h0, h1);
      h0 = h_unit<G0, U0, 0>(pk, hr0); h1 = h_unit<G0, U0, 1>(pk, hr1);
      TB_STEP(1, false);
      h_store(hp + c1, h2, h3);
      h2 = h_unit<G0 + 4, U0 + 4, 0>(pk, hr0); h3 = h_unit<G0 + 4, U0 + 4, 1>(pk, hr1);
      TB_REL(1);
    }
#pragma unroll 1
    for (int u = 2; u < 10; u++) {
      TB_STEP(u, false);
      if (u < 4) { h_store(hrow + (2 * bj + 1) * 8192 + (u & 1) * c1, h0, h1); h0 = h2; h1 = h3; if (u == 3) bar_arrive(2, 288); }
      TB_REL(u);
      if (u == 6 && tid_all == 256) post_max(FL_T2, e, clk() - t_start);
    }
    mbar_wait(sb + B_PAR2, 0);
    wg_fence();
    mma_n192_ext<0>(accB, ea0, ea1, desc(HBE, sb + BEXT + 256 * 16));
    wg_commit();
    wg_wait<1>();
    release2(sb + B_EMPTY1 + 8 * (19 & 3), tid);
    wg_wait<0>();
    if (tid_all == 256) TS(23);
    uint8_t* hpB = hrow + (16 + bj) * 8192;
    uint8_t* hpC = hrow + (24 + (bj >> 1)) * 8192 + (bj & 1) * c1;
    constexpr int GC = GF ? 16 : 20, UC = GF ? 20 : 16;
    float G[40];
    uint32_t sv[20];
#define G2_STEP(FIRST)                                                                   \
      {                                                                                  \
        mbar_wait(sb + B_FULL2 + 8 * bs, ph);                                            \
        const uint32_t st = sb + RING + sl * 28672;                                      \
        const uint64_t da = desc(HH, st), db = desc(HB2, st + 8192);                     \
        wg_fence();                                                                      \
        if (FIRST) mma_n160_first<0>(accG, da, db); else mma_n160(accG, da, db, 1);      \
        mma_n160(accG, da + 16, db + 64, 1);                                             \
        mma_n160(accG, da + 256, db + 640, 1);                                            \
        mma_n160(accG, da + 272, db + 704, 1);                                            \
        wg_commit();                                                                     \
      }
#define G2_NEXT(REL)                                                                     \
      {                                                                                  \
        wg_wait<1>();                                                                    \
        if (REL) release(sb + B_EMPTY2 + 8 * (bs ? bs - 1 : 5), tid); \
        if (++sl == 6) sl = 0;                                                           \
        if (++bs == 6) { bs = 0; ph ^= 1; }                                              \
      }
    if (w == 0) {
#pragma unroll
      for (int i = 0; i < 48; i++) pk[i] = pack_bf16(accB[2 * i], accB[2 * i + 1]);
      float accG[80];
      int sl = 3, bs = 0, ph = 0;
      bar_arrive(5, 256);
      mbar_wait(sb + B_TG, 0);
      wait_until(lds32(sb + TGV));
      if (tid == 0) TS(47);
      G2_STEP(true);
      sl = 4; bs = 1;
      G2_STEP(false);
      h_store(hpB, h_unit<G0, U0, 0>(pk, hr0), h_unit<G0, U0, 1>(pk, hr1));
      h0 = h_unit<G0 + 4, U0 + 4, 0>(pk, hr0);
      G2_NEXT(true); G2_STEP(false);
      h_store(hpB + c1, h0, h_unit<G0 + 4, U0 + 4, 1>(pk, hr1));
      if (bj < 6) h_store(hpC, h_unit<GC, UC, 0>(pk, hr0), h_unit<GC, UC, 1>(pk, hr1));
      bar_arrive(3, 288);
#pragma unroll 1
      for (int m = 3; m < 27; m++) {
        G2_NEXT(m < 23);
        if (m == 23 && tid == 0) mbar_arrive(sb + B_XFREE);
        G2_STEP(false);
      }
      wg_wait<0>();
      if (tid == 0) TS(24);
#pragma unroll
      for (int i = 0; i < 10; i++) {
        sts128(sb + RING + 28672 + (i * 128 + tid) * 16, __float_as_uint(accG[8 * i + 2]), __float_as_uint(accG[8 * i + 3]), __float_as_uint(accG[8 * i + 6]), __float_as_uint(accG[8 * i + 7]));
        G[4 * i] = accG[8 * i]; G[4 * i + 1] = accG[8 * i + 1]; G[4 * i + 2] = accG[8 * i + 4]; G[4 * i + 3] = accG[8 * i + 5];
      }
      bar_sync(12, 256);
#pragma unroll
      for (int p = 0; p < 5; p++) { const uint4 t = lds128(sb + SIDE + 32768 + (p * 128 + tid) * 16); sv[4 * p] = t.x; sv[4 * p + 1] = t.y; sv[4 * p + 2] = t.z; sv[4 * p + 3] = t.w; }
    } else {
      h_store(hpB, h_unit_acc<G0, U0, 0>(accB, hr0), h_unit_acc<G0, U0, 1>(accB, hr1));
      h_store(hpB + c1, h_unit_acc<G0 + 4, U0 + 4, 0>(accB, hr0), h_unit_acc<G0 + 4, U0 + 4, 1>(accB, hr1));
      if (bj < 6) h_store(hpC, h_unit_acc<GC, UC, 0>(accB, hr0), h_unit_acc<GC, UC, 1>(accB, hr1));
      bar_arrive(3, 288);
      bar_sync(5, 256);
      if (wi == 0) { e_expect(sb + B_D64, 8192); e_bulk(sb + BEXT, g_tab + TAB_D64 + tt * 2048, 8192, sb + B_D64); }
      mbar_wait(sb + B_WRDY, 0);
      const float ks = __uint_as_float(max(lds32(sb + FEV), 2u) << 23) * (64.f / 320.f);
      mbar_wait(sb + B_D64, 0);
      float accP[80];
      constexpr uint64_t HY = desc_hi(16, 1024, 1), HM = desc_hi(512, 128, 0);
#define P4_GEMM(Q, SLOT, PH)                                                                   \
      {                                                                                        \
        mbar_wait(sb + B_P4 + 8 * (SLOT), PH);                                                 \
        uint64_t da = desc(HY, sb + SIDE + (SLOT) * 16384), db = desc(HM, sb + BEXT);          \
        wg_fence();                                                                            \
        mma_n32t_first<16 * (Q)>(accP, da, db);                                                \
        _Pragma("unroll") for (int k = 1; k < 8; k++) { da += 128; db += 64; mma_n32t<16 * (Q)>(accP, da, db, 1); } \
        wg_commit();                                                                           \
      }
      P4_GEMM(1, 0, 0);
      P4_GEMM(2, 1, 0);
      P4_GEMM(3, 2, 0);
      wg_wait<1>();
      if (tid == 0) mbar_arrive(sb + B_P4F);
      P4_GEMM(4, 0, 1);
      P4_GEMM(0, 1, 1);
      wg_wait<0>();
      if (tid == 0) TS(45);
#pragma unroll 1
      for (int rh = 0; rh < 2; rh++) {
#pragma unroll
        for (int a = 0; a < 4; a++) {
          const float2 tw = cispi((16 * tt + 4 * a + lam) * (1.f / 160.f));
          const float2 t1 = make_float2(tw.x * ks, tw.y * ks), t2 = cmul(t1, tw), t3 = cmul(t2, tw), t4 = cmul(t3, tw);
          const int o = 4 * a;
          const float2 u0 = make_float2(accP[o] * ks, accP[o + 1] * ks);
          const float2 u1 = cmul(make_float2(accP[16 + o], accP[17 + o]), t1), u2 = cmul(make_float2(accP[32 + o], accP[33 + o]), t2);
          const float2 u3 = cmul(make_float2(accP[48 + o], accP[49 + o]), t3), u4 = cmul(make_float2(accP[64 + o], accP[65 + o]), t4);
          const float k1 = 0.30901699437494742f, k2 = -0.80901699437494742f, s1 = 0.95105651629515357f, s2 = 0.58778525229247313f;
          const float2 a1 = make_float2(u1.x + u4.x, u1.y + u4.y), a2 = make_float2(u2.x + u3.x, u2.y + u3.y);
          const float2 b1 = make_float2(u1.x - u4.x, u1.y - u4.y), b2 = make_float2(u2.x - u3.x, u2.y - u3.y);
          const float2 m1 = make_float2(fmaf(k2, a2.x, fmaf(k1, a1.x, u0.x)), fmaf(k2, a2.y, fmaf(k1, a1.y, u0.y)));
          const float2 m2 = make_float2(fmaf(k1, a2.x, fmaf(k2, a1.x, u0.x)), fmaf(k1, a2.y, fmaf(k2, a1.y, u0.y)));
          const float2 n1 = make_float2(fmaf(s2, b2.x, s1 * b1.x), fmaf(s2, b2.y, s1 * b1.y));
          const float2 n2 = make_float2(fmaf(-s1, b2.x, s2 * b1.x), fmaf(-s1, b2.y, s2 * b1.y));
          sv[a] = pack_bf16(u0.x + a1.x + a2.x, u0.y + a1.y + a2.y);
          sv[4 + a] = pack_bf16(m1.x - n1.y, m1.y + n1.x);
          sv[16 + a] = pack_bf16(m1.x + n1.y, m1.y - n1.x);
          sv[8 + a] = pack_bf16(m2.x - n2.y, m2.y + n2.x);
          sv[12 + a] = pack_bf16(m2.x + n2.y, m2.y - n2.x);
        }
        if (rh == 0) {
#pragma unroll
          for (int p = 0; p < 5; p++) sts128(sb + SIDE + 32768 + (p * 128 + tid) * 16, sv[4 * p], sv[4 * p + 1], sv[4 * p + 2], sv[4 * p + 3]);
#pragma unroll
          for (int i = 0; i < 20; i++) { accP[4 * i] = accP[4 * i + 2]; accP[4 * i + 1] = accP[4 * i + 3]; }
        }
      }
      if (tid == 0) TS(29);
      bar_sync(12, 256);
#pragma unroll
      for (int i = 0; i < 10; i++) {
        const uint4 t = lds128(sb + RING + 28672 + (i * 128 + tid) * 16);
        G[4 * i] = __uint_as_float(t.x); G[4 * i + 1] = __uint_as_float(t.y); G[4 * i + 2] = __uint_as_float(t.z); G[4 * i + 3] = __uint_as_float(t.w);
      }
    }
    mbar_wait(sb + B_XFULL, 0);
    if (tid_all == 256) TS(25);
    const uint32_t xt = sb + RING + wi * 1024 + w * 512, xa = xt + (lane & 7) * 64 + (((lane >> 3) ^ ((lane >> 1) & 3)) << 4);
#pragma unroll
    for (int p = 0; p < 5; p++) {
      const uint4 x4 = ldsm4(xa + p * 4096);
      const uint32_t xx[4] = {x4.x, x4.y, x4.z, x4.w};
      uint32_t o[4];
#pragma unroll
      for (int a = 0; a < 4; a++) {
        const uint32_t gb = pack_bf16(G[8 * p + 2 * a], G[8 * p + 2 * a + 1]);
        const float h0 = 0.5f * bf_lo(gb), h1 = 0.5f * bf_hi(gb);
        o[a] = hadd2_bf(xx[a], hmul2_bf(sv[4 * p + a], pack_bf16(fmaf(tanh_fast(h0), h0, h0), fmaf(tanh_fast(h1), h1, h1))));
      }
      stsm4(xa + p * 4096, o[0], o[1], o[2], o[3]);
      fence_async_smem();
      __syncwarp();
      e_tma2d_st(&P.mout, xt + p * 4096, 128 * p + 32 * tt, rt2 * 64 + 16 * wi + 8 * w);
    }
    bulk_commit(); bulk_wait_read();
    if (tid_all == 256) TS(26);
  }
}

typedef CUresult (*EncodeFn)(CUtensorMap*, CUtensorMapDataType, cuuint32_t, void*, const cuuint64_t*, const cuuint64_t*, const cuuint32_t*,
                             const cuuint32_t*, CUtensorMapInterleave, CUtensorMapSwizzle, CUtensorMapL2promotion, CUtensorMapFloatOOBfill);

}

extern "C" void kernel_launch(void* const* d_in, const int* in_sizes, int n_in, void* d_out, int out_size) {
  (void)in_sizes; (void)n_in; (void)out_size;
  static EncodeFn enc = nullptr;
  if (!enc) {
    void* fn = nullptr; cudaDriverEntryPointQueryResult q;
    cudaGetDriverEntryPoint("cuTensorMapEncodeTiled", &fn, cudaEnableDefault, &q);
    enc = (EncodeFn)fn;
    cudaFuncSetAttribute(fused_kernel<true>, cudaFuncAttributeMaxDynamicSharedMemorySize, SMEM_BYTES);
    cudaFuncSetAttribute(fused_kernel<false>, cudaFuncAttributeMaxDynamicSharedMemorySize, SMEM_BYTES);
  }
  Params P;
  P.x = (const __nv_bfloat16*)d_in[0]; P.wr = (const __nv_bfloat16*)d_in[1]; P.wi = (const __nv_bfloat16*)d_in[2];
  const __nv_bfloat16 *wgate = (const __nv_bfloat16*)d_in[4], *wup = (const __nv_bfloat16*)d_in[5];
  const bool gf = wgate < wup;
  P.w0 = gf ? wgate : wup; P.w1 = gf ? wup : wgate;
  P.wd = (const __nv_bfloat16*)d_in[6];
  const cuuint64_t dlt = (cuuint64_t)((const char*)P.w1 - (const char*)P.w0);
  void *zptr = nullptr, *yptr = nullptr, *cptr = nullptr;
  cudaGetSymbolAddress(&zptr, g_z); cudaGetSymbolAddress(&yptr, g_y); cudaGetSymbolAddress(&cptr, g_wc);
  auto mk = [&](CUtensorMap* m, CUtensorMapDataType ty, int rank, const void* base, const cuuint64_t* dims, const cuuint64_t* str, const cuuint32_t* box, CUtensorMapSwizzle sw) {
    const cuuint32_t es[5] = {1, 1, 1, 1, 1};
    enc(m, ty, rank, (void*)base, dims, str, box, es, CU_TENSOR_MAP_INTERLEAVE_NONE, sw, CU_TENSOR_MAP_L2_PROMOTION_L2_256B, CU_TENSOR_MAP_FLOAT_OOB_FILL_NONE);
  };
  const CUtensorMapDataType BF = CU_TENSOR_MAP_DATA_TYPE_BFLOAT16;
  { const cuuint64_t d[2] = {D_, S_}, st[1] = {D_ * 2}; const cuuint32_t b[2] = {64, 128}, b2[2] = {32, 64}, b3[2] = {32, 8};
    mk(&P.mx, BF, 2, P.x, d, st, b, CU_TENSOR_MAP_SWIZZLE_128B);
    mk(&P.mxf, BF, 2, P.x, d, st, b2, CU_TENSOR_MAP_SWIZZLE_64B);
    mk(&P.mout, BF, 2, d_out, d, st, b3, CU_TENSOR_MAP_SWIZZLE_64B); }
  { const cuuint64_t d[3] = {F_, D_, 2}, st[2] = {F_ * 2, dlt}; const cuuint32_t b[3] = {64, 64, 2}, b2[3] = {32, 64, 2};
    mk(&P.mw, BF, 3, P.w0, d, st, b, CU_TENSOR_MAP_SWIZZLE_128B);
    mk(&P.mwh, BF, 3, P.w0, d, st, b2, CU_TENSOR_MAP_SWIZZLE_NONE); }
  { const cuuint64_t d[4] = {32, 64, 2, 60}, st[3] = {128, 64, 8192}; const cuuint32_t b[4] = {32, 64, 2, 1};
    mk(&P.mcs, BF, 4, cptr, d, st, b, CU_TENSOR_MAP_SWIZZLE_NONE);
    const cuuint64_t d2[2] = {64, 3840}, st2[1] = {128}; const cuuint32_t b2[2] = {64, 64};
    mk(&P.mcl, BF, 2, cptr, d2, st2, b2, CU_TENSOR_MAP_SWIZZLE_128B); }
  { const cuuint64_t d[5] = {128, 2, F_ / 8, 4, 5}, st[4] = {D_ * 2, D_ * 16, D_ * 4, 256}; const cuuint32_t b[5] = {32, 2, 4, 4, 5};
    mk(&P.mwd, BF, 5, d_in[6], d, st, b, CU_TENSOR_MAP_SWIZZLE_64B); }
  { const cuuint64_t d[3] = {16, 320, 128}, st[2] = {64, 20480}; const cuuint32_t b[3] = {16, 1, 128};
    mk(&P.mz, CU_TENSOR_MAP_DATA_TYPE_UINT32, 3, zptr, d, st, b, CU_TENSOR_MAP_SWIZZLE_NONE); }
  { const cuuint64_t d[4] = {64, 128, 5, 32}, st[3] = {128, 16384, 81920}; const cuuint32_t b[4] = {64, 2, 1, 32};
    mk(&P.my, BF, 4, yptr, d, st, b, CU_TENSOR_MAP_SWIZZLE_NONE); }
  cudaLaunchConfig_t cfg = {};
  cudaLaunchAttribute at[1];
  at[0].id = cudaLaunchAttributeClusterDimension; at[0].val.clusterDim.x = 2; at[0].val.clusterDim.y = 1; at[0].val.clusterDim.z = 1;
  cfg.attrs = at; cfg.numAttrs = MC;
  cfg.gridDim = dim3(128); cfg.blockDim = dim3(512); cfg.dynamicSmemBytes = SMEM_BYTES; cfg.stream = cudaStreamPerThread;

  if (gf) cudaLaunchKernelEx(&cfg, fused_kernel<true>, P);
  else cudaLaunchKernelEx(&cfg, fused_kernel<false>, P);
}
```
